```python
import torch

def _softmax(x, axis=-1):
    return torch.softmax(x, dim=axis)

def _gelu(x):
    return torch.nn.functional.gelu(x, approximate='tanh')

def _silu(x):
    return torch.nn.functional.silu(x)

def _sigmoid(x):
    return torch.sigmoid(x)

def _layernorm(x, axis=-1, eps=1e-05):
    m = x.mean(dim=axis, keepdim=True)
    v = x.var(dim=axis, keepdim=True, unbiased=False)
    return (x - m) / torch.sqrt(v + eps)

def _scatter_add(tgt, idx, src, axis=0):
    return tgt.clone().index_add_(axis, idx, src)

def _segment_sum(src, seg, n):
    out = torch.zeros((n,) + src.shape[1:], dtype=src.dtype)
    return out.index_add_(0, seg, src)

def _pad(x, pw):
    flat = tuple((v for pair in reversed(pw) for v in pair))
    return torch.nn.functional.pad(x, flat)
kernel_name = 'adaLN_cond__linear_kernel_hedgehog__glu_gated_reglu__prompt'

def setup_inputs():

    _w = lambda a: (lambda t: t.to(torch.bfloat16) if t.is_floating_point() else t)(torch.as_tensor(a))

    def _A_setup():
        B, S, D, H = (1, 2048, 512, 32)
        Dh = D // H
        return {'x': _w((lambda *s: torch.randn(*s, dtype=torch.bfloat16) * 0.05)(B, S, D)), 'wqkv': _w((lambda *s: torch.randn(*s, dtype=torch.bfloat16) * 0.4)(D, 3 * D)), 'w_phi': _w((lambda *s: torch.randn(*s, dtype=torch.bfloat16) * 0.4)(H, Dh, Dh) * Dh ** (-0.5)), 'wo': _w((lambda *s: torch.randn(*s, dtype=torch.bfloat16) * 0.05)(D, D))}
    _A_in = _A_setup()

    def _B_setup():
        B, S, D, F = (1, 2048, 512, 1792)
        return {'x': _w((lambda *s: torch.randn(*s, dtype=torch.bfloat16) * 0.05)(B, S, D)), 'W_gate': _w((lambda *s: torch.randn(*s, dtype=torch.bfloat16) * 0.8)(D, F) * (2.0 / D) ** 0.5), 'W_up': _w((lambda *s: torch.randn(*s, dtype=torch.bfloat16) * 0.8)(D, F) * (2.0 / D) ** 0.5), 'W_down': _w((lambda *s: torch.randn(*s, dtype=torch.bfloat16) * 0.8)(F, D) * (1.0 / F) ** 0.5)}
    _B_in = _B_setup()
    return {'A_x': _A_in['x'], 'A_wqkv': _A_in['wqkv'], 'A_w_phi': _A_in['w_phi'], 'A_wo': _A_in['wo'], 'B_x': _B_in['x'], 'B_W_gate': _B_in['W_gate'], 'B_W_up': _B_in['W_up'], 'B_W_down': _B_in['W_down'], 'c': _w((lambda *s: torch.randn(*s, dtype=torch.bfloat16) * 0.2)(1, 512) * 8.0), 'w_mod': _w((lambda *s: torch.randn(*s, dtype=torch.bfloat16) * 0.2)(512, 6 * 512) * 512 ** (-0.5) * 8.0)}

def reference(A_x, A_wqkv, A_w_phi, A_wo, B_x, B_W_gate, B_W_up, B_W_down, c, w_mod):

    def _A_ref(x, wqkv, w_phi, wo):
        B, S, D = x.shape
        H = 32
        Dh = D // H
        qkv = (lambda x, *d: x.permute(*d))((x @ wqkv).reshape(B, S, 3, H, Dh), 2, 0, 3, 1, 4)
        q, k, v = (qkv[0], qkv[1], qkv[2])
        pq = torch.einsum('bhsd,hdf->bhsf', q, w_phi)
        pk = torch.einsum('bhsd,hdf->bhsf', k, w_phi)
        phi_q = torch.concatenate([_softmax(pq, axis=-1), _softmax(-pq, axis=-1)], axis=-1)
        phi_k = torch.concatenate([_softmax(pk, axis=-1), _softmax(-pk, axis=-1)], axis=-1)
        kv = torch.einsum('bhsf,bhsd->bhfd', phi_k, v)
        z = torch.einsum('bhsf->bhf', phi_k)
        num = torch.einsum('bhqf,bhfd->bhqd', phi_q, kv)
        den = torch.einsum('bhqf,bhf->bhq', phi_q, z)[..., None] + 1e-06
        o = num / den
        return (lambda x, *d: x.permute(*d))(o, 0, 2, 1, 3).reshape(B, S, D) @ wo

    def _B_ref(x, W_gate, W_up, W_down):
        gate = torch.einsum('bsd,df->bsf', x, W_gate)
        up = torch.einsum('bsd,df->bsf', x, W_up)
        gate = gate * (lambda x, dt: x.to(dt))(gate > 0, gate.dtype)
        h = gate * up
        return torch.einsum('bsf,fd->bsd', h, W_down)
    x = A_x
    mod = (_silu(c) @ w_mod).reshape(c.shape[0], 6, 1, -1)
    sa, ca, ga, sb, cb, gb = (mod[:, 0].clone(), mod[:, 1].clone(), mod[:, 2].clone(), mod[:, 3].clone(), mod[:, 4].clone(), mod[:, 5].clone())
    h = _layernorm(x, axis=-1) * (1 + ca) + sa
    x = x + ga * _A_ref(h, A_wqkv, A_w_phi, A_wo)
    h = _layernorm(x, axis=-1) * (1 + cb) + sb
    x = x + gb * _B_ref(h, B_W_gate, B_W_up, B_W_down)
    return x
```

```cpp
#include <cuda_runtime.h>
#include <cuda_bf16.h>
#include <cuda.h>
#include <stdint.h>

namespace {

constexpr int SLOT = 16384;
constexpr int OFF_PHIB = 13 * SLOT;
constexpr int OFF_TAB1 = OFF_PHIB + 8192;
constexpr int OFF_TAB2 = OFF_TAB1 + 2048;
constexpr int OFF_SC = OFF_TAB2 + 2048;
constexpr int OFF_GAB = OFF_SC + 512;
constexpr int OFF_RED = OFF_GAB + 512;
constexpr int OFF_BAR = OFF_RED + 2048;
constexpr int SMEM_BYTES = OFF_BAR + 2048;

enum {
  B_XF = 0, B_WF = 8, B_XRF = 12, B_WOF = 13, B_RF = 16, B_OF = 160, B_X1F = 168,
  B_RE = 80, B_KVP2 = B_RE + 32, B_NUME = B_RE + 34, B_WOE = B_RE + 36, B_WOE1 = B_RE + 38,
  B_XE2 = 128, B_XRE = 129, B_X1E = 130,
  B_KDONE = 136, B_QDONE = 137, B_KVP = 138, B_DONE = 139, B_HST = 140,
  B_XE = 144, B_ZERO = 145, B_KVB = 146, B_MOD1 = 147, B_MOD2 = 148, B_ISS = 149, B_HS = 152, B_END = 176
};

struct __align__(128) Half {
  uint4 o[8][512], x1[8][512];
  uint4 y[8][512];
  float2 st2[8][64];
  uint2 fo[32], fx[32];
};
struct __align__(128) Scratch {
  uint32_t epoch[32];
  uint32_t fh[16][8][4][2];
  float mod[4][3072];
  float4 kv[8][768];
  Half half[32];
  uint4 h[16][28][1024];
};
__device__ Scratch g_scratch;

struct Params {
  CUtensorMap x3, wqkv, x, wo, wg, wu, wg32, wu32, wd, out;
  const __nv_bfloat16 *wop, *wgp, *wup, *wdp;
};

#define TS(role, i)
#define TSC(i)
#define TSG(i)
#define SMEM_EXTRA 0

#define POLLAT 7
#define W1AT 2
#define W1LN 20
#define FMTH 6
#define PHIK 0
#define WOLATE
#define YAT 5
#define MC 1
#define X1EF 1
#define AWIN 3
#define WVL 0
#define WQL 0
#define PFV 1
#define SD 400
#define ST2 0
#define P1A 1
#define SK 0
#define SKD 1
#define PROD 0
#define SPINT 1
#define GX0 2
#define GX1 -1
#define GO0 -1
#define PD 0
#define SAT 0
#define Y2 0
#define NT 1
#define R13 0
#define XR 0
#define KV2 0
#define NUMO 1
#define TW -1
#define NB 0
#define CKO 1
#define HOLD -1
#define XH0 -1
#define XH1 0
#define TBI 2
#define XD 0
#define G1 1
#define WKL 0
#define W2G 3
#define QH 5
#define EO 2
#define EX 1
#define AGD 0
#define KVD 1300
#define M2D 0
__device__ __forceinline__ void mbar_init(uint32_t b, uint32_t c) { asm volatile("mbarrier.init.shared::cta.b64 [%0], %1;" ::"r"(b), "r"(c) : "memory"); }
__device__ __forceinline__ void mbar_expect(uint32_t b, uint32_t bytes) { asm volatile("mbarrier.arrive.expect_tx.shared::cta.b64 _, [%0], %1;" ::"r"(b), "r"(bytes) : "memory"); }
__device__ __forceinline__ void mbar_arrive(uint32_t b) { asm volatile("mbarrier.arrive.shared::cta.b64 _, [%0];" ::"r"(b) : "memory"); }
__device__ __forceinline__ void mbar_arrive_n(uint32_t b, uint32_t n) { asm volatile("mbarrier.arrive.shared::cta.b64 _, [%0], %1;" ::"r"(b), "r"(n) : "memory"); }
__device__ __forceinline__ void mbar_arrive_pair(uint32_t b, uint32_t rd) {
  asm volatile("mbarrier.arrive.shared::cta.b64 _, [%0];\nmbarrier.arrive.shared::cluster.b64 _, [%1];" ::"r"(b), "r"(b + rd) : "memory");
}
__device__ __forceinline__ void mbar_waitb(uint32_t b) {
  asm volatile(
      "{\n.reg .pred p;\n.reg .u32 n;\nmov.u32 n, 0;\n"
      "LW:\nmbarrier.try_wait.parity.shared::cta.b64 p, [%0], 0;\n@p bra LD;\n"
      "add.u32 n, n, 1;\nsetp.lt.u32 p, n, 4000000;\n@p bra LW;\ntrap;\nLD:\n}" ::"r"(b) : "memory");
}
__device__ __forceinline__ void mbar_wait(uint32_t b) {
  asm volatile("{\n.reg .pred p;\nLW:\nmbarrier.try_wait.parity.shared::cta.b64 p, [%0], 0;\n@!p bra LW;\n}" ::"r"(b) : "memory");
}
__device__ __forceinline__ void mbar_wait_cl(uint32_t b) {
  asm volatile("{\n.reg .pred p;\nLW:\nmbarrier.try_wait.parity.acquire.cluster.shared::cta.b64 p, [%0], 0;\n@!p bra LW;\n}" ::"r"(b) : "memory");
}
__device__ __forceinline__ uint32_t clock32() { uint32_t c; asm volatile("mov.u32 %0, %%clock;" : "=r"(c)); return c; }
__device__ __forceinline__ void delay(uint32_t d) {
  uint32_t c0, c1;
  asm volatile("mov.u32 %0, %%clock;" : "=r"(c0));
  do { asm volatile("mov.u32 %0, %%clock;" : "=r"(c1)); } while (c1 - c0 < d);
}
__device__ __forceinline__ bool elect() {
  uint32_t p;
  asm volatile("{\n.reg .pred p;\nelect.sync _|p, 0xffffffff;\nselp.u32 %0, 1, 0, p;\n}" : "=r"(p));
  return p;
}
__device__ __forceinline__ void bar_sync(int id, int n) { asm volatile("bar.sync %0, %1;" ::"r"(id), "r"(n) : "memory"); }
__device__ __forceinline__ void wg_bar(int wg) {
  if (wg) asm volatile("bar.sync 9, 128;" ::: "memory");
  else asm volatile("bar.sync 8, 128;" ::: "memory");
}
__device__ __forceinline__ void bar_arrive(int id, int n) { asm volatile("bar.arrive %0, %1;" ::"r"(id), "r"(n) : "memory"); }
#define ELECT "{\n.reg .pred p;\nelect.sync _|p, 0xffffffff;\n@p "
__device__ __forceinline__ void tma2d(uint32_t dst, const void* m, int c0, int c1, uint32_t bar) {
  asm volatile(ELECT "cp.async.bulk.tensor.2d.shared::cluster.global.mbarrier::complete_tx::bytes [%0], [%1, {%3, %4}], [%2];\n}"
               ::"r"(dst), "l"(m), "r"(bar), "r"(c0), "r"(c1) : "memory");
}
__device__ __forceinline__ void tma2d_mc(uint32_t dst, const void* m, int c0, int c1, uint32_t bar) {
  asm volatile(ELECT "cp.async.bulk.tensor.2d.shared::cluster.global.mbarrier::complete_tx::bytes.multicast::cluster [%0], [%1, {%3, %4}], [%2], %5;\n}"
               ::"r"(dst), "l"(m), "r"(bar), "r"(c0), "r"(c1), "h"((uint16_t)3) : "memory");
}
#define FOR_R for (int r = rk, r1 = 0; r1 < 1; r1++)
#define tma2d_w tma2d_mc
__device__ __forceinline__ void tma3d(uint32_t dst, const CUtensorMap* m, int c0, int c1, int c2, uint32_t bar) {
  asm volatile(ELECT "cp.async.bulk.tensor.3d.shared::cluster.global.mbarrier::complete_tx::bytes [%0], [%1, {%3, %4, %5}], [%2];\n}"
               ::"r"(dst), "l"(m), "r"(bar), "r"(c0), "r"(c1), "r"(c2) : "memory");
}
__device__ __forceinline__ void bulk_ld(uint32_t dst, const void* src, uint32_t bytes, uint32_t bar) {
  asm volatile(ELECT "cp.async.bulk.shared::cluster.global.mbarrier::complete_tx::bytes [%0], [%1], %2, [%3];\n}"
               ::"r"(dst), "l"(src), "r"(bytes), "r"(bar) : "memory");
}
__device__ __forceinline__ void bulk_st(void* dst, uint32_t src, uint32_t bytes) {
  asm volatile(ELECT "cp.async.bulk.global.shared::cta.bulk_group [%0], [%1], %2;\n}" ::"l"(dst), "r"(src), "r"(bytes) : "memory");
}
__device__ __forceinline__ void l2_prefetch(const void* p, uint32_t bytes) { asm volatile(ELECT "cp.async.bulk.prefetch.L2.global [%0], %1;\n}" ::"l"(p), "r"(bytes) : "memory"); }
__device__ __forceinline__ void fence_async_smem() { asm volatile("fence.proxy.async.shared::cta;" ::: "memory"); }
__device__ __forceinline__ void wg_fence() { asm volatile("wgmma.fence.sync.aligned;" ::: "memory"); }
__device__ __forceinline__ void wg_commit() { asm volatile("wgmma.commit_group.sync.aligned;" ::: "memory"); }
template <int N> __device__ __forceinline__ void wg_wait() { asm volatile("wgmma.wait_group.sync.aligned %0;" ::"n"(N) : "memory"); }
template <int N> __device__ __forceinline__ void pin(float (&d)[N]) {
#pragma unroll
  for (int i = 0; i < N; i++) asm volatile("" : "+f"(d[i])::"memory");
}
template <int A, int B, int N> __device__ __forceinline__ void pin_range(float (&d)[N]) {
#pragma unroll
  for (int i = A; i < B; i++) asm volatile("" : "+f"(d[i])::"memory");
}
__device__ __forceinline__ uint64_t mkdesc(uint32_t sb, uint32_t off, uint32_t lbo, uint32_t sbo, uint32_t mode, uint32_t dyn = 0) {
  uint32_t lo = (((sb & 0x3ffff) >> 4) + dyn) + ((off >> 4) + ((lbo >> 4) << 16)), hi = (sbo >> 4) | (mode << 30);
  return (uint64_t)lo | ((uint64_t)hi << 32);
}
__device__ __forceinline__ uint32_t pack2(float lo, float hi) { uint32_t r; asm("cvt.rn.bf16x2.f32 %0, %1, %2;" : "=r"(r) : "f"(hi), "f"(lo)); return r; }
__device__ __forceinline__ float bflo(uint32_t v) { return __uint_as_float(v << 16); }
__device__ __forceinline__ float bfhi(uint32_t v) { return __uint_as_float(v & 0xffff0000u); }
__device__ __forceinline__ uint32_t hfma2(uint32_t a, uint32_t b, uint32_t c) { uint32_t r; asm("fma.rn.bf16x2 %0, %1, %2, %3;" : "=r"(r) : "r"(a), "r"(b), "r"(c)); return r; }
__device__ __forceinline__ float ex2(float x) { float r; asm("ex2.approx.ftz.f32 %0, %1;" : "=f"(r) : "f"(x)); return r; }
__device__ __forceinline__ float rcp(float x) { float r; asm("rcp.approx.ftz.f32 %0, %1;" : "=f"(r) : "f"(x)); return r; }
__device__ __forceinline__ void hmma(float (&c)[4], uint32_t a0, uint32_t a1, uint32_t a2, uint32_t a3, uint32_t b0, uint32_t b1) {
  asm volatile("mma.sync.aligned.m16n8k16.row.col.f32.bf16.bf16.f32 {%0,%1,%2,%3}, {%4,%5,%6,%7}, {%8,%9}, {%0,%1,%2,%3};"
               : "+f"(c[0]), "+f"(c[1]), "+f"(c[2]), "+f"(c[3]) : "r"(a0), "r"(a1), "r"(a2), "r"(a3), "r"(b0), "r"(b1));
}
__device__ __forceinline__ void hmma8(float (&c)[4], uint32_t a0, uint32_t a1, uint32_t b0) {
  asm volatile("mma.sync.aligned.m16n8k8.row.col.f32.bf16.bf16.f32 {%0,%1,%2,%3}, {%4,%5}, {%6}, {%0,%1,%2,%3};"
               : "+f"(c[0]), "+f"(c[1]), "+f"(c[2]), "+f"(c[3]) : "r"(a0), "r"(a1), "r"(b0));
}
__device__ __forceinline__ uint32_t movtrans(uint32_t v) {
  uint32_t r;
  asm volatile("movmatrix.sync.aligned.m8n8.trans.b16 %0, %1;" : "=r"(r) : "r"(v));
  return r;
}
__device__ __forceinline__ void stg128(void* p, const uint32_t (&r)[4]) {
  asm volatile("st.global.v4.u32 [%0], {%1,%2,%3,%4};" ::"l"(p), "r"(r[0]), "r"(r[1]), "r"(r[2]), "r"(r[3]) : "memory");
}
__device__ __forceinline__ void ldsm4(uint32_t (&r)[4], uint32_t a) {
  asm volatile("ldmatrix.sync.aligned.m8n8.x4.shared.b16 {%0,%1,%2,%3}, [%4];" : "=r"(r[0]), "=r"(r[1]), "=r"(r[2]), "=r"(r[3]) : "r"(a) : "memory");
}
__device__ __forceinline__ void stsm4(uint32_t a, uint32_t r0, uint32_t r1, uint32_t r2, uint32_t r3) {
  asm volatile("stmatrix.sync.aligned.m8n8.x4.shared.b16 [%0], {%1,%2,%3,%4};" ::"r"(a), "r"(r0), "r"(r1), "r"(r2), "r"(r3) : "memory");
}
__device__ __forceinline__ void lds128(uint32_t (&r)[4], uint32_t a) {
  asm volatile("ld.shared.v4.u32 {%0,%1,%2,%3}, [%4];" : "=r"(r[0]), "=r"(r[1]), "=r"(r[2]), "=r"(r[3]) : "r"(a) : "memory");
}
template <int OFF>
__device__ __forceinline__ void lds128i(uint32_t (&r)[4], uint32_t a) {
  asm volatile("ld.shared.v4.u32 {%0,%1,%2,%3}, [%4+%5];" : "=r"(r[0]), "=r"(r[1]), "=r"(r[2]), "=r"(r[3]) : "r"(a), "n"(OFF) : "memory");
}
template <int K, int N, int F0>
__device__ __forceinline__ void lds_frags(uint32_t (&af)[32][4], uint32_t a) {
  if constexpr (K < N) {
    lds128i<(K >> 2) * 8192 + (K & 3) * 512>(af[F0 + K], a);
    lds_frags<K + 1, N, F0>(af, a);
  }
}
__device__ __forceinline__ float2 lds64f(uint32_t a) { float2 r; asm volatile("ld.shared.v2.f32 {%0,%1}, [%2];" : "=f"(r.x), "=f"(r.y) : "r"(a) : "memory"); return r; }
__device__ __forceinline__ uint32_t lds32(uint32_t a) { uint32_t r; asm volatile("ld.shared.u32 %0, [%1];" : "=r"(r) : "r"(a) : "memory"); return r; }
__device__ __forceinline__ void sts128(uint32_t a, uint32_t x, uint32_t y, uint32_t z, uint32_t w) {
  asm volatile("st.shared.v4.u32 [%0], {%1,%2,%3,%4};" ::"r"(a), "r"(x), "r"(y), "r"(z), "r"(w) : "memory");
}
__device__ __forceinline__ void sts64(uint32_t a, uint32_t x, uint32_t y) { asm volatile("st.shared.v2.u32 [%0], {%1,%2};" ::"r"(a), "r"(x), "r"(y) : "memory"); }
__device__ __forceinline__ void sts32(uint32_t a, uint32_t x) { asm volatile("st.shared.u32 [%0], %1;" ::"r"(a), "r"(x) : "memory"); }
__device__ __forceinline__ uint4 ldg_nc(const void* p) {
  uint4 v; asm volatile("ld.global.L1::no_allocate.L2::128B.v4.u32 {%0,%1,%2,%3}, [%4];" : "=r"(v.x), "=r"(v.y), "=r"(v.z), "=r"(v.w) : "l"(p) : "memory"); return v;
}
__device__ __forceinline__ uint32_t ldg32(const void* p) { uint32_t v; asm volatile("ld.global.u32 %0, [%1];" : "=r"(v) : "l"(p) : "memory"); return v; }
__device__ __forceinline__ uint32_t ldg16(const void* p) { uint32_t v; asm volatile("ld.global.u16 %0, [%1];" : "=r"(v) : "l"(p) : "memory"); return v; }
__device__ __forceinline__ void ld_rlx128(uint32_t (&r)[4], const void* p) {
  asm volatile("ld.relaxed.gpu.global.v4.u32 {%0,%1,%2,%3}, [%4];" : "=r"(r[0]), "=r"(r[1]), "=r"(r[2]), "=r"(r[3]) : "l"(p) : "memory");
}
__device__ __forceinline__ uint2 ld_rlx64(const void* p) {
  unsigned long long a;
  asm volatile("ld.relaxed.gpu.global.b64 %0, [%1];" : "=l"(a) : "l"(p) : "memory");
  return make_uint2((uint32_t)a, (uint32_t)(a >> 32));
}
__device__ __forceinline__ uint32_t ld_rlx32(const void* p) { uint32_t v; asm volatile("ld.relaxed.gpu.global.u32 %0, [%1];" : "=r"(v) : "l"(p) : "memory"); return v; }
__device__ __forceinline__ uint32_t ld_acq32(const void* p) { uint32_t v; asm volatile("ld.acquire.gpu.global.u32 %0, [%1];" : "=r"(v) : "l"(p) : "memory"); return v; }
__device__ __forceinline__ void st_rlx64(void* p, uint32_t x, uint32_t y) {
  asm volatile("st.relaxed.gpu.global.b64 [%0], %1;" ::"l"(p), "l"((unsigned long long)x | ((unsigned long long)y << 32)) : "memory");
}
__device__ __forceinline__ void st_rlx32(void* p, uint32_t x) { asm volatile("st.relaxed.gpu.global.u32 [%0], %1;" ::"l"(p), "r"(x) : "memory"); }
__device__ __forceinline__ void st_rel32(void* p, uint32_t x) { asm volatile("st.release.gpu.global.u32 [%0], %1;" ::"l"(p), "r"(x) : "memory"); }
__device__ __forceinline__ void spin_check(uint32_t& n) {
  asm volatile("{\n.reg .pred p;\nadd.u32 %0, %0, 1;\nsetp.gt.u32 p, %0, 20000000;\n@p trap;\n}" : "+r"(n));
}

__device__ __forceinline__ void mma_rs_n64(float (&d)[32], const uint32_t (&a)[4], uint64_t db, int sd) {
  asm volatile("{\n.reg .pred p;\nsetp.ne.b32 p, %37, 0;\n"
    "wgmma.mma_async.sync.aligned.m64n64k16.f32.bf16.bf16 "
    "{%0, %1, %2, %3, %4, %5, %6, %7, %8, %9, %10, %11, %12, %13, %14, %15, "
    "%16, %17, %18, %19, %20, %21, %22, %23, %24, %25, %26, %27, %28, %29, %30, %31}, "
    "{%32, %33, %34, %35}, %36, p, 1, 1, 1;\n}"
    : "+f"(d[0]), "+f"(d[1]), "+f"(d[2]), "+f"(d[3]), "+f"(d[4]), "+f"(d[5]), "+f"(d[6]), "+f"(d[7]),
      "+f"(d[8]), "+f"(d[9]), "+f"(d[10]), "+f"(d[11]), "+f"(d[12]), "+f"(d[13]), "+f"(d[14]), "+f"(d[15]),
      "+f"(d[16]), "+f"(d[17]), "+f"(d[18]), "+f"(d[19]), "+f"(d[20]), "+f"(d[21]), "+f"(d[22]), "+f"(d[23]),
      "+f"(d[24]), "+f"(d[25]), "+f"(d[26]), "+f"(d[27]), "+f"(d[28]), "+f"(d[29]), "+f"(d[30]), "+f"(d[31])
    : "r"(a[0]), "r"(a[1]), "r"(a[2]), "r"(a[3]), "l"(db), "r"(sd));
}
__device__ __forceinline__ void mma_rs_n128(float (&d)[64], const uint32_t (&a)[4], uint64_t db, int sd) {
  asm volatile("{\n.reg .pred p;\nsetp.ne.b32 p, %69, 0;\n"
    "wgmma.mma_async.sync.aligned.m64n128k16.f32.bf16.bf16 "
    "{%0, %1, %2, %3, %4, %5, %6, %7, %8, %9, %10, %11, %12, %13, %14, %15, "
    "%16, %17, %18, %19, %20, %21, %22, %23, %24, %25, %26, %27, %28, %29, %30, %31, "
    "%32, %33, %34, %35, %36, %37, %38, %39, %40, %41, %42, %43, %44, %45, %46, %47, "
    "%48, %49, %50, %51, %52, %53, %54, %55, %56, %57, %58, %59, %60, %61, %62, %63}, "
    "{%64, %65, %66, %67}, %68, p, 1, 1, 1;\n}"
    : "+f"(d[0]), "+f"(d[1]), "+f"(d[2]), "+f"(d[3]), "+f"(d[4]), "+f"(d[5]), "+f"(d[6]), "+f"(d[7]),
      "+f"(d[8]), "+f"(d[9]), "+f"(d[10]), "+f"(d[11]), "+f"(d[12]), "+f"(d[13]), "+f"(d[14]), "+f"(d[15]),
      "+f"(d[16]), "+f"(d[17]), "+f"(d[18]), "+f"(d[19]), "+f"(d[20]), "+f"(d[21]), "+f"(d[22]), "+f"(d[23]),
      "+f"(d[24]), "+f"(d[25]), "+f"(d[26]), "+f"(d[27]), "+f"(d[28]), "+f"(d[29]), "+f"(d[30]), "+f"(d[31]),
      "+f"(d[32]), "+f"(d[33]), "+f"(d[34]), "+f"(d[35]), "+f"(d[36]), "+f"(d[37]), "+f"(d[38]), "+f"(d[39]),
      "+f"(d[40]), "+f"(d[41]), "+f"(d[42]), "+f"(d[43]), "+f"(d[44]), "+f"(d[45]), "+f"(d[46]), "+f"(d[47]),
      "+f"(d[48]), "+f"(d[49]), "+f"(d[50]), "+f"(d[51]), "+f"(d[52]), "+f"(d[53]), "+f"(d[54]), "+f"(d[55]),
      "+f"(d[56]), "+f"(d[57]), "+f"(d[58]), "+f"(d[59]), "+f"(d[60]), "+f"(d[61]), "+f"(d[62]), "+f"(d[63])
    : "r"(a[0]), "r"(a[1]), "r"(a[2]), "r"(a[3]), "l"(db), "r"(sd));
}
__device__ __forceinline__ void mma_ss_n128(float (&d)[64], uint64_t da, uint64_t db, int sd) {
  asm volatile("{\n.reg .pred p;\nsetp.ne.b32 p, %66, 0;\n"
    "wgmma.mma_async.sync.aligned.m64n128k16.f32.bf16.bf16 "
    "{%0, %1, %2, %3, %4, %5, %6, %7, %8, %9, %10, %11, %12, %13, %14, %15, "
    "%16, %17, %18, %19, %20, %21, %22, %23, %24, %25, %26, %27, %28, %29, %30, %31, "
    "%32, %33, %34, %35, %36, %37, %38, %39, %40, %41, %42, %43, %44, %45, %46, %47, "
    "%48, %49, %50, %51, %52, %53, %54, %55, %56, %57, %58, %59, %60, %61, %62, %63}, "
    "%64, %65, p, 1, 1, 0, 1;\n}"
    : "+f"(d[0]), "+f"(d[1]), "+f"(d[2]), "+f"(d[3]), "+f"(d[4]), "+f"(d[5]), "+f"(d[6]), "+f"(d[7]),
      "+f"(d[8]), "+f"(d[9]), "+f"(d[10]), "+f"(d[11]), "+f"(d[12]), "+f"(d[13]), "+f"(d[14]), "+f"(d[15]),
      "+f"(d[16]), "+f"(d[17]), "+f"(d[18]), "+f"(d[19]), "+f"(d[20]), "+f"(d[21]), "+f"(d[22]), "+f"(d[23]),
      "+f"(d[24]), "+f"(d[25]), "+f"(d[26]), "+f"(d[27]), "+f"(d[28]), "+f"(d[29]), "+f"(d[30]), "+f"(d[31]),
      "+f"(d[32]), "+f"(d[33]), "+f"(d[34]), "+f"(d[35]), "+f"(d[36]), "+f"(d[37]), "+f"(d[38]), "+f"(d[39]),
      "+f"(d[40]), "+f"(d[41]), "+f"(d[42]), "+f"(d[43]), "+f"(d[44]), "+f"(d[45]), "+f"(d[46]), "+f"(d[47]),
      "+f"(d[48]), "+f"(d[49]), "+f"(d[50]), "+f"(d[51]), "+f"(d[52]), "+f"(d[53]), "+f"(d[54]), "+f"(d[55]),
      "+f"(d[56]), "+f"(d[57]), "+f"(d[58]), "+f"(d[59]), "+f"(d[60]), "+f"(d[61]), "+f"(d[62]), "+f"(d[63])
    : "l"(da), "l"(db), "r"(sd));
}
__device__ __forceinline__ void mma_ss_n64(float (&d)[32], uint64_t da, uint64_t db, int sd) {
  asm volatile("{\n.reg .pred p;\nsetp.ne.b32 p, %34, 0;\n"
    "wgmma.mma_async.sync.aligned.m64n64k16.f32.bf16.bf16 "
    "{%0, %1, %2, %3, %4, %5, %6, %7, %8, %9, %10, %11, %12, %13, %14, %15, "
    "%16, %17, %18, %19, %20, %21, %22, %23, %24, %25, %26, %27, %28, %29, %30, %31}, "
    "%32, %33, p, 1, 1, 0, 1;\n}"
    : "+f"(d[0]), "+f"(d[1]), "+f"(d[2]), "+f"(d[3]), "+f"(d[4]), "+f"(d[5]), "+f"(d[6]), "+f"(d[7]),
      "+f"(d[8]), "+f"(d[9]), "+f"(d[10]), "+f"(d[11]), "+f"(d[12]), "+f"(d[13]), "+f"(d[14]), "+f"(d[15]),
      "+f"(d[16]), "+f"(d[17]), "+f"(d[18]), "+f"(d[19]), "+f"(d[20]), "+f"(d[21]), "+f"(d[22]), "+f"(d[23]),
      "+f"(d[24]), "+f"(d[25]), "+f"(d[26]), "+f"(d[27]), "+f"(d[28]), "+f"(d[29]), "+f"(d[30]), "+f"(d[31])
    : "l"(da), "l"(db), "r"(sd));
}
__device__ __forceinline__ void mma_ss_n40t(float (&d)[20], uint64_t da, uint64_t db, int sd) {
  asm volatile("{\n.reg .pred p;\nsetp.ne.b32 p, %22, 0;\n"
    "wgmma.mma_async.sync.aligned.m64n40k16.f32.bf16.bf16 "
    "{%0, %1, %2, %3, %4, %5, %6, %7, %8, %9, %10, %11, %12, %13, %14, %15, "
    "%16, %17, %18, %19}, "
    "%20, %21, p, 1, 1, 1, 1;\n}"
    : "+f"(d[0]), "+f"(d[1]), "+f"(d[2]), "+f"(d[3]), "+f"(d[4]), "+f"(d[5]), "+f"(d[6]), "+f"(d[7]),
      "+f"(d[8]), "+f"(d[9]), "+f"(d[10]), "+f"(d[11]), "+f"(d[12]), "+f"(d[13]), "+f"(d[14]), "+f"(d[15]),
      "+f"(d[16]), "+f"(d[17]), "+f"(d[18]), "+f"(d[19])
    : "l"(da), "l"(db), "r"(sd));
}
__device__ __forceinline__ void mma_ss_n24(float (&d)[12], uint64_t da, uint64_t db, int sd) {
  asm volatile("{\n.reg .pred p;\nsetp.ne.b32 p, %14, 0;\n"
    "wgmma.mma_async.sync.aligned.m64n24k16.f32.bf16.bf16 "
    "{%0, %1, %2, %3, %4, %5, %6, %7, %8, %9, %10, %11}, "
    "%12, %13, p, 1, 1, 0, 1;\n}"
    : "+f"(d[0]), "+f"(d[1]), "+f"(d[2]), "+f"(d[3]), "+f"(d[4]), "+f"(d[5]), "+f"(d[6]), "+f"(d[7]),
      "+f"(d[8]), "+f"(d[9]), "+f"(d[10]), "+f"(d[11])
    : "l"(da), "l"(db), "r"(sd));
}

#define U_(x) __uint_as_float(x)
#define F_(x) __uint_as_float((x) & ~1u)
__device__ __forceinline__ uint32_t px2(uint32_t a, uint32_t b, uint32_t p) { uint32_t r; asm("lop3.b32 %0, %1, %2, %3, 0x7e;" : "=r"(r) : "r"(a), "r"(b), "r"(p)); return r; }
__device__ __forceinline__ uint32_t px4(uint32_t a, uint32_t b, uint32_t c, uint32_t d, uint32_t p, uint32_t acc = 0) {
  uint32_t r;
  asm("lop3.b32 %0, %1, %2, %3, 0xfe;" : "=r"(r) : "r"(px2(a, b, p)), "r"(px2(c, d, p)), "r"(acc));
  return r;
}
__device__ __forceinline__ uint32_t lane_id() { uint32_t l; asm volatile("mov.u32 %0, %%laneid;" : "=r"(l)); return l; }
__device__ __forceinline__ uint32_t mat_off(int ww, uint32_t l) { return (ww * 16 + (l & 15)) * 128 + (((l >> 4) ^ (l & 7)) << 4); }
__device__ __forceinline__ uint32_t launch_parity(uint32_t epoch) {
  uint32_t par;
  asm volatile("{\n.reg .pred p;\nsetp.ne.u32 p, %1, 0;\nvote.sync.any.pred p, p, 0xffffffff;\nselp.u32 %0, 0, 1, p;\n}" : "=r"(par) : "r"(epoch & 1));
  return par;
}
__device__ __forceinline__ uint32_t tagu(uint32_t v, uint32_t par) { uint32_t r; asm("bfi.b32 %0, %1, %2, 0, 1;" : "=r"(r) : "r"(par), "r"(v)); return r; }
__device__ __forceinline__ uint32_t tagf(float v, uint32_t par) { return tagu(__float_as_uint(v), par); }
__device__ __forceinline__ int x_slot(int c) { return c < 6 ? 3 + c : 2 * c - 2; }
__device__ __forceinline__ int wa_slot(int a) { return a < 3 ? a : (a == 3 ? 11 : x_slot(a - 4)); }
__device__ __forceinline__ int ring_prev(int u) {
  const int v = u < 39 ? u - 9 : (R13 && u > 41 ? max(u - 13, 30) : max(u - 11, 29));
  return v >= 31 ? 31 + ((v - 31) & ~1) : v;
}
__device__ __forceinline__ int f_base(int j, int p) { return 224 * j + ((j & 1) ? (p < 3 ? 32 + 64 * p : 0) : 64 * p); }

constexpr int S_T = 12 - NT, U_T = 25 + 2 * S_T, U_N = U_T + 3 * NT;
__host__ __device__ constexpr int slot_of(int u) {
  return u < 37 ? u % 9 : (int)((R13 ? 0x87654ca3b921ull >> (4 * ((u - 37) % 13)) : 0x0876543b921ull >> (4 * ((u - 37) % 11))) & 15);
}
__host__ __device__ constexpr uint64_t slot_pack(int u0, int du, int n) { return n ? slot_of(u0) | slot_pack(u0 + du, du, n - 1) << 4 : 0; }
struct Load { uint32_t wait, dst, full; int c0, c1, src; };
__device__ __forceinline__ Load ffn_load(int i, int j, int r) {
  Load e;
  int u, off;
  const bool w = i < 46;
  if (i < 32) {
    const int p = i & 7;
    u = e.full = i < 24 ? i : 24 + p / 2;
    e.c0 = f_base(j, i >> 3);
    e.c1 = (p ? (p - 1 + (p - 1 >= j)) : j) * 64;
    off = i < 24 ? r * 8192 : (p & 1) * 8192 + r * 4096;
    e.src = (i < 24 ? 4 : 6) + r;
  } else {
    const int t = w ? i - 32 : i - 43, s = (w || t < S_T) ? t : (t < S_T + 2 * NT ? S_T + (t - S_T) / 2 : t - NT);
    const int q = s % 3, p = s < 3 ? s : s / 3 - 1, x = s >= S_T && (w ? r : (t - S_T) & 1);
    const int js = (s < 3 ? j : (j & 4) + q + (q >= (j & 3))) ^ (4 * x);
    off = w ? r * 8192 : 0;
    if (s < 12) {
      u = s < 3 ? 28 + s : (s < S_T ? 25 + 2 * s + w : U_T + 3 * (s - S_T) + (w ? 1 : 2 * x));
      e.full = u - (w && s >= 3 && s < S_T);
      e.c0 = w ? (r || s >= S_T ? j : j ^ 4) * 64 : 1 << (js * 4 + p);
      e.c1 = f_base(js, p);
      e.src = w ? 8 : p * 8 + js;
    } else {
      u = e.full = U_N + (w ? 3 * (s - 12) : s - 11 + (s >= 14));
      e.c0 = w ? j * 64 : 0x88u << (8 * (s & 3));
      e.c1 = 192 + 448 * (2 * s - 24 + r);
      e.src = w ? 8 : 12 + s;
    }
  }
  e.dst = slot_of(u) * SLOT + off;
  e.wait = OFF_BAR + 8 * (u < 6 ? (u < 2 ? (u ? B_XRE : B_NUME) : B_WOE + 2 * (u >> 2)) : (u < 9 ? B_X1E + u - 6 : B_RE + ring_prev(u)));
  e.full = OFF_BAR + 8 * (B_RF + e.full);
  return e;
}
__device__ __forceinline__ void mbar_spin(uint32_t b) {
  asm volatile("{\n.reg .pred p;\nLW:\nmbarrier.test_wait.parity.shared::cta.b64 p, [%0], 0;\n@!p bra LW;\n}" ::"r"(b) : "memory");
}
__device__ __forceinline__ bool mbar_test(uint32_t b) {
  uint32_t ok;
  asm volatile("{\n.reg .pred p;\nmbarrier.test_wait.parity.shared::cta.b64 p, [%1], 0;\nselp.u32 %0, 1, 0, p;\n}" : "=r"(ok) : "r"(b) : "memory");
  return ok;
}

__device__ __forceinline__ void ln_rows(uint32_t (&a)[4], const uint32_t (&s)[4]) {
  a[0] = hfma2(a[0], s[0], s[1]);
  a[1] = hfma2(a[1], s[2], s[3]);
  a[2] = hfma2(a[2], s[0], s[1]);
  a[3] = hfma2(a[3], s[2], s[3]);
}
__device__ __forceinline__ void ln_cols(uint32_t (&a)[4], const uint32_t (&t)[4]) {
  a[0] = hfma2(a[0], t[0], t[1]);
  a[1] = hfma2(a[1], t[0], t[1]);
  a[2] = hfma2(a[2], t[2], t[3]);
  a[3] = hfma2(a[3], t[2], t[3]);
}

template <int A0>
__device__ __forceinline__ void pass64(float (&acc)[32], uint32_t (&af)[32][4], uint32_t sb) {
  wg_fence();
#pragma unroll
  for (int k = 0; k < 32; k++) {
    if (A0 == 0 && k == 16) mbar_wait(sb + OFF_BAR + 8 * (B_WF + 1));
    mma_rs_n64(acc, af[k], mkdesc(sb, wa_slot(A0 + k / 8) * SLOT + (k & 7) * 2048, 0, 1024, 1), k > 0);
  }
  wg_commit();
}

__device__ __forceinline__ void check4(uint32_t (*a)[4], const uint4* gp, uint32_t off, uint32_t par) {
  asm volatile(
      "{\n.reg .pred p;\n.reg .u32 t, u;\n.reg .u64 g;\n"
      "LC:\nlop3.b32 t, %0, %4, %18, 0x7e;\nlop3.b32 u, %8, %12, %18, 0x7e;\nlop3.b32 t, t, u, 1, 0xa8;\nsetp.ne.u32 p, t, 0;\n"
      "vote.sync.any.pred p, p, 0xffffffff;\n@!p bra LD;\n"
      "mov.u32 t, %%laneid;\nadd.u32 t, t, %17;\nmad.wide.u32 g, t, 16, %16;\n"
      "ld.relaxed.gpu.global.v4.u32 {%0, %1, %2, %3}, [g];\nld.relaxed.gpu.global.v4.u32 {%4, %5, %6, %7}, [g+512];\n"
      "ld.relaxed.gpu.global.v4.u32 {%8, %9, %10, %11}, [g+1024];\nld.relaxed.gpu.global.v4.u32 {%12, %13, %14, %15}, [g+1536];\n"
      "bra LC;\nLD:\nand.b32 %0, %0, 0xfffffffe;\nand.b32 %4, %4, 0xfffffffe;\nand.b32 %8, %8, 0xfffffffe;\nand.b32 %12, %12, 0xfffffffe;\n}"
      : "+r"(a[0][0]), "+r"(a[0][1]), "+r"(a[0][2]), "+r"(a[0][3]), "+r"(a[1][0]), "+r"(a[1][1]), "+r"(a[1][2]), "+r"(a[1][3]),
        "+r"(a[2][0]), "+r"(a[2][1]), "+r"(a[2][2]), "+r"(a[2][3]), "+r"(a[3][0]), "+r"(a[3][1]), "+r"(a[3][2]), "+r"(a[3][3])
      : "l"(gp), "r"(off), "r"(par)
      : "memory");
}

template <int Q>
__device__ __forceinline__ float extremum(const float (&p)[32]) {
  float m[8];
#pragma unroll
  for (int i = 0; i < 8; i++) m[i] = (Q & 1) ? fminf(p[4 * i + (Q & 2)], p[4 * i + (Q & 2) + 1]) : fmaxf(p[4 * i + (Q & 2)], p[4 * i + (Q & 2) + 1]);
#pragma unroll
  for (int w = 4; w; w >>= 1)
#pragma unroll
    for (int i = 0; i < w; i++) m[i] = (Q & 1) ? fminf(m[i], m[i + w]) : fmaxf(m[i], m[i + w]);
  return m[0];
}

__device__ __forceinline__ void feature_map(float (&acc)[32], uint32_t sb, uint32_t st0, int wg, int it) {
  uint32_t kf[4][4];
#pragma unroll
  for (int h = 0; h < 4; h++)
#pragma unroll
    for (int i = 0; i < 4; i++) kf[h][i] = pack2(acc[8 * h + 2 * i], acc[8 * h + 2 * i + 1]);
  float p[32];
  wg_fence();
#pragma unroll
  for (int h = 0; h < 4; h++) mma_rs_n64(p, kf[h], mkdesc(sb, OFF_PHIB + h * 2048, 1024, 128, 0), h > 0);
  wg_commit();
  if (!wg && (it ? QH == 0 : PHIK)) bar_arrive(4, 256);
  const uint32_t lane = lane_id(), sw = (((lane & 1) << 2) ^ (lane & 2) ^ (lane >> 2)) << 4;
  st0 += (lane & 2) * 4096 + (lane >> 2) * 128;
  wg_wait<0>();
  pin(p);
  TSC(it ? 26 : 29);
  const float L = 1.4426950408889634f;
  float off = extremum<0>(p) * -L, e[2][16], s;
#pragma unroll
  for (int q = 0; q < 5; q++) {
    float inv = 0.f, off2 = off;
    if (q) {
      inv = rcp(s);
      off2 = fmaf(inv, 0.f, off);
    }
    if (QH && q == QH && !wg && it) bar_arrive(4, 256);
    if (q < 4) {
#pragma unroll
      for (int i = 0; i < 16; i++) e[q & 1][i] = ex2(fmaf(p[4 * (i >> 1) + (q & 2) + (i & 1)], (q & 1) ? -L : L, i >= FMTH ? off2 : off));
    }
    if (q == 0) off = extremum<1>(p) * L;
    if (q == 1) off = extremum<2>(p) * -L;
    if (q == 2) off = extremum<3>(p) * L;
    if (q) {
      const float* v = e[(q - 1) & 1];
#pragma unroll
      for (int u = 0; u < 2; u++)
        sts128(st0 + ((q - 1) >> 1) * 1024 + (((2 * ((q - 1) & 1) + u) << 4) ^ sw), pack2(v[8 * u] * inv, v[8 * u + 1] * inv),
               pack2(v[8 * u + 2] * inv, v[8 * u + 3] * inv), pack2(v[8 * u + 4] * inv, v[8 * u + 5] * inv), pack2(v[8 * u + 6] * inv, v[8 * u + 7] * inv));
    }
    if (q < 4) {
      s = e[q & 1][0];
#pragma unroll
      for (int i = 1; i < 16; i++) s += e[q & 1][i];
    }
  }
  if (QH == 5 && !wg && it) bar_arrive(4, 256);
  fence_async_smem();
}

__device__ __forceinline__ void glu_epilogue(float (&acc)[64], uint32_t relbar, uint32_t rd, bool lead, uint32_t ha, int ww, uint32_t donebar) {
  const uint32_t lane = lane_id(), mo = mat_off(ww, lane);
  wg_wait<0>();
  pin(acc);
  if (lead) mbar_arrive_pair(relbar, rd);
#pragma unroll
  for (int k = 0; k < 4; k++) {
    uint32_t h[4];
#pragma unroll
    for (int i = 0; i < 4; i++)
      h[i] = pack2(fmaxf(acc[8 * k + 2 * i], 0.f) * acc[32 + 8 * k + 2 * i], fmaxf(acc[8 * k + 2 * i + 1], 0.f) * acc[33 + 8 * k + 2 * i]);
    stsm4(ha + (mo ^ (k << 5)), h[0], h[1], h[2], h[3]);
  }
  fence_async_smem();
  __syncwarp();
  if (lane == 0) mbar_arrive_n(donebar, 2);
}

__device__ __forceinline__ uint32_t mod_bad(const uint32_t (&v)[4][4], uint32_t par) {
  uint32_t bad = 0;
#pragma unroll
  for (int q = 0; q < 4; q++) bad = px4(v[q][0], v[q][1], v[q][2], v[q][3], par, bad);
  return bad & 1;
}
__device__ __forceinline__ uint2 mod_sum(const uint32_t (&v)[4][4]) {
  float s[4];
#pragma unroll
  for (int e = 0; e < 4; e++) s[e] = (F_(v[0][e]) + F_(v[1][e])) + (F_(v[2][e]) + F_(v[3][e]));
  return make_uint2(pack2(s[0], s[1]), pack2(s[2], s[3]));
}
__device__ __forceinline__ void mod_collect(const float* mp, int o1, uint32_t par, uint2& u, uint2& v) {
  uint32_t m0[4][4], m1[4][4], n = 0;
  do {
#pragma unroll
    for (int q = 0; q < 4; q++) {
      ld_rlx128(m0[q], mp + q * 3072);
      ld_rlx128(m1[q], mp + q * 3072 + o1);
    }
    spin_check(n);
  } while (__any_sync(~0u, mod_bad(m0, par) | mod_bad(m1, par)));
  u = mod_sum(m0);
  v = mod_sum(m1);
}
__device__ __forceinline__ void put_tab(uint32_t tab, int u, uint2 sh, uint2 sc) {
  const uint32_t ad = tab + (u >> 2) * 64 + (u & 1) * 32 + (u & 2) * 4;
  sts64(ad, pack2(1.f + bflo(sc.x), 1.f + bfhi(sc.x)), sh.x);
  sts64(ad + 16, pack2(1.f + bflo(sc.y), 1.f + bfhi(sc.y)), sh.y);
}

__global__ void __cluster_dims__(2, 1, 1) __launch_bounds__(384, 1) fused_kernel(Scratch* const G, const __nv_bfloat16* __restrict__ wmod,
    const __nv_bfloat16* __restrict__ cvec, const __nv_bfloat16* __restrict__ wphi, const __grid_constant__ Params P) {
  extern __shared__ __align__(1024) unsigned char smem[];
  const uint32_t sb = (uint32_t)__cvta_generic_to_shared(smem);
  const int tid = threadIdx.x, lane = tid & 31;
  const int warp = __shfl_sync(0xffffffffu, tid >> 5, 0);
  const int wg = warp >> 2;
  const int cl = blockIdx.x >> 1, rk = blockIdx.x & 1;
  int ti, j;
  if (cl < 4) { ti = 7; j = 4 + cl; }
  else if (cl < 36) { ti = (cl - 4) & 7; j = (cl - 4) >> 3; }
  else { ti = (cl - 36) % 7; j = 4 + (cl - 36) / 7; }
  ti = 2 * ti + rk;
  const int b = ti * 8 + j, kq = b & 3, cg = b >> 2;
  const uint32_t bar0 = sb + OFF_BAR;
#define BAR(x) (bar0 + 8 * (x))
  uint32_t rd;
  asm("mapa.shared::cluster.u32 %0, %1, %2;" : "=r"(rd) : "r"(sb), "r"(rk ^ 1));
  rd -= sb;

  if (wg == 2) {
    asm volatile("setmaxnreg.dec.sync.aligned.u32 56;");
    const int hw = warp - 8, ht = tid - 256;
    if (elect()) {
      if (hw == 0) {
        asm volatile("prefetch.tensormap [%0];" ::"l"(&P.x3) : "memory");
        asm volatile("prefetch.tensormap [%0];" ::"l"(&P.wqkv) : "memory");
      }
      const int i0 = hw < 2 ? 16 * hw : 48 * hw - 16, i1 = hw < 2 ? 16 + 64 * hw : 32 + 48 * hw;
#pragma unroll 1
      for (int i = i0; i < i1; i += 8) {
        const uint32_t cnt = hw < 2 ? 1 : (hw == 2 ? 2 << MC : (i == B_XE2 ? 8 << MC : (i == B_KDONE ? 2 : (i < B_OF ? 8 : 1))));
#pragma unroll
        for (int k = 0; k < 8; k++) mbar_init(BAR(i + k), cnt);
      }
      asm volatile("fence.mbarrier_init.release.cluster;" ::: "memory");
    }
    __syncwarp();
    if (hw == 0) {
      if (lane < 14) mbar_expect(BAR(lane), (lane == 8 || lane == 9) ? 2 * SLOT : ((lane == 10 || lane == 11 || lane == 13) ? 4 * SLOT : SLOT));
    } else if (hw == 1) {
      mbar_expect(BAR(16 + lane), lane == 31 ? 2 * SLOT : SLOT);
      mbar_expect(BAR(48 + lane), lane < U_T - 32 ? 2 * SLOT : SLOT);
    }
    if (hw == 3 && lane < 16) mbar_expect(BAR(B_OF + lane), (lane & 3) ? SLOT : 8192);
    asm volatile("barrier.cluster.arrive.relaxed.aligned;" ::: "memory");
    if (ht == 32) TS(2, 11);
    if (hw == 0) {
      bar_sync(11, G1 ? 288 : 160);
      if (XD) delay(XD);
      if (lane == 0) TS(2, 6);
#pragma unroll
      for (int c = 0; c < 8; c++) tma3d(sb + x_slot(c) * SLOT, &P.x3, 0, ti * 128 + (c >> 2) * 64, (c & 3) * 2, BAR(B_XF + c));
      asm volatile(ELECT "cp.async.bulk.prefetch.tensor.2d.L2.global [%0, {%1, %2}];\n}" ::"l"(&P.wqkv), "r"(512 + j * 64), "r"((ti & 3) * 128) : "memory");
      if (lane == 0) TS(2, 7);
    }
    const uint32_t par = launch_parity(ld_rlx32(G->epoch));
      if (hw < 2) st_rlx32(&G->mod[kq][1024 + 64 * cg + ht], par ^ 1);
    if (hw == 3) {
      G->kv[j][48 * ti + lane] = make_float4(0.f, 0.f, 0.f, par ? 32.f : 0.f);
      if (lane < 16) G->kv[j][48 * ti + 32 + lane] = make_float4(0.f, 0.f, 0.f, par ? 32.f : 0.f);
    }
    if (hw == 2 && elect()) {
#pragma unroll 1
      for (int i = 0; i < 8; i++) asm volatile("prefetch.tensormap [%0];" ::"l"(&P.x + i) : "memory");
    }
    __syncwarp();
    asm volatile("barrier.cluster.wait.aligned;" ::: "memory");
    if (ht == 64) TS(2, 10);
    {
      mbar_waitb(BAR(B_XF + POLLAT));
      uint32_t m0[4][4], m1[4][4], n = 0;
      const float* mp = &G->mod[0][4 * ht];
      do {
#pragma unroll
        for (int q = 0; q < 4; q++) {
          ld_rlx128(m0[q], mp + q * 3072);
          ld_rlx128(m1[q], mp + q * 3072 + 512);
        }
        if (hw == 0 && n == 0) {
          FOR_R tma2d_w(sb + r * SLOT, &P.wqkv, 512 + j * 64, r * 128, BAR(B_WF));
          FOR_R tma2d_w(sb + (2 + 9 * r) * SLOT, &P.wqkv, 512 + j * 64, 256 + r * 128, BAR(B_WF + 1));
        }
        spin_check(n);
      } while (__any_sync(~0u, mod_bad(m0, par) | mod_bad(m1, par)));
      put_tab(sb + OFF_TAB1, ht, mod_sum(m0), mod_sum(m1));
      __syncwarp();
      if (lane == 0) mbar_arrive_n(BAR(B_MOD1), 2);
    }
    if (ht == 32) TS(2, 5);
#define LOAD_W(a) FOR_R tma2d_w(sb + (r ? x_slot(2 * (a) + 1) : x_slot(2 * (a))) * SLOT, &P.wqkv, ((a) < 2 ? 1024 : 0) + j * 64, (((a) & 1) * 2 + r) * 128, BAR(B_WF + 2 + (a) / 2))
    if (hw == 0) {
      asm volatile(ELECT "cp.async.bulk.prefetch.tensor.2d.L2.global [%0, {%1, %2}];\n}" ::"l"(&P.wqkv), "r"((ti & 4) * 256 + j * 64), "r"((ti & 3) * 128) : "memory");
      mbar_waitb(BAR(B_XE2));
      LOAD_W(0);
      LOAD_W(1);
      LOAD_W(2);
      LOAD_W(3);
    }
    mbar_waitb(BAR(B_WF + W2G - 1));
    uint4 w2[8];
    {
      const __nv_bfloat16* wp = wmod + (size_t)(kq * 128 + hw * 32 + (lane >> 3)) * 3072 + 1024 + 64 * cg + (lane & 7) * 8;
#pragma unroll
      for (int i = 0; i < 8; i++) w2[i] = ldg_nc(wp + i * 4 * 3072);
    }
    {
      float a[8];
#pragma unroll
      for (int e = 0; e < 8; e++) a[e] = 0.f;
#pragma unroll
      for (int it = 0; it < 8; it++) {
        const uint32_t w[4] = {w2[it].x, w2[it].y, w2[it].z, w2[it].w};
        const uint32_t sp = lds32(sb + OFF_SC + 2 * (hw * 32 + (lane >> 4) * 2 + 4 * it));
        const float s = (lane & 8) ? bfhi(sp) : bflo(sp);
#pragma unroll
        for (int e = 0; e < 4; e++) {
          a[2 * e] = fmaf(s, bflo(w[e]), a[2 * e]);
          a[2 * e + 1] = fmaf(s, bfhi(w[e]), a[2 * e + 1]);
        }
      }
#pragma unroll
      for (int i = 0; i < 4; i++) { const bool hi = lane & 16; a[i] = (hi ? a[i + 4] : a[i]) + __shfl_xor_sync(~0u, hi ? a[i] : a[i + 4], 16); }
#pragma unroll
      for (int i = 0; i < 2; i++) { const bool hi = lane & 8; a[i] = (hi ? a[i + 2] : a[i]) + __shfl_xor_sync(~0u, hi ? a[i] : a[i + 2], 8); }
      sts64(sb + OFF_RED + 512 + hw * 256 + ((lane & 7) * 8 + (lane >> 3) * 2) * 4, __float_as_uint(a[0]), __float_as_uint(a[1]));
      bar_sync(12, 128);
      if (hw < 2) {
        const uint32_t ra = sb + OFF_RED + 512 + ht * 4;
        st_rlx32(&G->mod[kq][1024 + 64 * cg + ht], tagf((U_(lds32(ra)) + U_(lds32(ra + 256))) + (U_(lds32(ra + 512)) + U_(lds32(ra + 768))), par));
      }
      *(uint2*)&G->half[2 * ti + (ht >> 6)].st2[j][ht & 63] = make_uint2(par ^ 1, par ^ 1);
      if (ht < 16) G->half[2 * ti + (ht >> 3)].fo[(ht & 4) * 8 + j * 4 + (ht & 3)] = make_uint2(par ^ 1, par ^ 1);
      if (hw == 2 && lane < 8) G->fh[ti][j][0][lane] = par ^ 1;
      if (ht == 32) TS(2, 1);
    }
    if (hw == 0) {
    }
    {
      mbar_waitb(BAR(B_WF + 3));
      if (lane == 0) TS(3, 20 + hw);
      if (hw == 1) {
        l2_prefetch((const char*)P.wop + b * 4096, 4096);
        l2_prefetch((const char*)P.wgp + b * 14336, 14336);
        l2_prefetch((const char*)P.wup + b * 14336, 14336);
        l2_prefetch((const char*)P.wdp + b * 14336, 14336);
      }
#pragma unroll 1
      for (int i = (XR & 2) ? 0 : 8; i < ((XR & 1) ? 16 : 8); i++)
        G->half[2 * ti + ((i >> 2) & 1)].o[(i & 8) + j][(i & 3) * 128 + ht] = make_uint4(par ^ 1, 0, 0, 0);
      {
        uint32_t n = 0;
        bool bad;
        do {
          bad = false;
#pragma unroll
          for (int i = 0; i < 6; i++) bad |= fabsf(U_(ld_rlx32(&G->kv[j][i * 128 + ht].w)) - (par ? 39.5f : 7.5f)) > 8.f;
          spin_check(n);
        } while (__any_sync(~0u, bad));
        if (lane == 0) mbar_arrive_n(BAR(B_ZERO), 2);
      }
      if (lane == 0) TS(3, 24 + hw);
      uint2 u, v;
      mod_collect(&G->mod[0][1536 + 4 * ht], 512, par, u, v);
      put_tab(sb + OFF_TAB2, ht, u, v);
      if (lane == 0) TS(2, 20 + hw);
      if (ht == 0) TS(2, 0);
    }
    mbar_waitb(BAR(B_KVP));
    if (ht == 32) TS(2, 2);
    const uint32_t kv0 = lds32(sb + OFF_RED);
    while (clock32() - kv0 < KVD) {}
    {
      uint32_t v[6][4], n = 0;
      const uint32_t full = par ? 0x42400000u : 0x41800000u;
      do {
#pragma unroll
        for (int i = 0; i < 6; i++) ld_rlx128(v[i], &G->kv[j][i * 128 + ht]);
        spin_check(n);
      } while (__any_sync(~0u, v[0][3] != full || v[1][3] != full || v[2][3] != full || v[3][3] != full || v[4][3] != full || v[5][3] != full));
      if (lane == 0) TS(2, 24 + hw);
#pragma unroll
      for (int w = 0; w < 2; w++) {
        const uint32_t ad = sb + (4 * w + hw) * 768 + (lane >> 2) * 16;
        sts32(ad + (lane & 3) * 4, pack2(U_(v[w][0]), U_(v[w][1])));
        sts32(ad + (lane & 3) * 4 + 384, pack2(U_(v[w][2]), U_(v[2 + w][0])));
        sts32(ad + (lane & 3) * 4 + 128, pack2(U_(v[2 + w][1]), U_(v[2 + w][2])));
        sts32(ad + (lane & 3) * 4 + 512, pack2(U_(v[4 + w][0]), U_(v[4 + w][1])));
        const uint32_t zz = pack2(U_(v[4 + w][2]), U_(v[4 + w][2]));
        sts64(ad + 256 + (lane & 1) * 384 + (lane & 2) * 4, zz, zz);
      }
      fence_async_smem();
      __syncwarp();
      if (lane == 0) mbar_arrive_n(BAR(B_KVB), 2);
    }
    if (ht == 32) TS(2, 4);
    asm volatile("setmaxnreg.dec.sync.aligned.u32 40;");

    if (hw == 0) {
      mbar_waitb(BAR(B_KVB));
#pragma unroll 1
      for (int p = MC * rk; p < 8; p += 1 + MC) tma2d_w(sb + 2 * SLOT + p * 8192, &P.wo, j * 64, (p ? (p - 1 + (p - 1 >= j)) : j) * 64, BAR(B_WOF));
      tma2d(sb + SLOT, &P.x, j * 64, ti * 128, BAR(B_XRF));
#pragma unroll 1
      for (int i0 = 0; i0 < 46; i0 += 23) {
        const Load e = ffn_load(min(i0 + lane, 45), j, rk);
        uint32_t i = 0, n = 0;
        while (i < 23) {
          uint32_t m = __ballot_sync(~0u, lane - i < 8u && mbar_test(sb + e.wait)) >> i;
          for (; i < 23 && (m & 1); i++, m >>= 1) {
            if (lane == i) {
              asm volatile("cp.async.bulk.tensor.2d.shared::cluster.global.mbarrier::complete_tx::bytes.multicast::cluster [%0], [%1, {%3, %4}], [%2], %5;"
                           ::"r"(sb + e.dst), "l"(&P.x3 + e.src), "r"(sb + e.full), "r"(e.c0), "r"(e.c1), "h"((uint16_t)3) : "memory");
              if (i0 + i < 12 || i0 + i >= 32) TS(2, i0 + i < 12 ? 32 + i : 12 + i0 + i);
            }
            __syncwarp();
          }
          spin_check(n);
        }
      }
    } else if (hw == 1) {
      {
        uint32_t m0[4][4], n = 0;
        const float* mp = &G->mod[0][(lane < 16 ? 1024 : 2560 - 64) + 64 * j + 4 * lane];
        do {
#pragma unroll
          for (int q = 0; q < 4; q++) ld_rlx128(m0[q], mp + q * 3072);
          spin_check(n);
        } while (__any_sync(~0u, mod_bad(m0, par)));
        const uint2 w = mod_sum(m0);
        sts128(sb + OFF_GAB + lane * 16, w.x << 16, w.x & 0xffff0000u, w.y << 16, w.y & 0xffff0000u);
        __syncwarp();
        if (lane == 0) mbar_arrive_n(BAR(B_MOD2), 8);
      }
      const uint32_t* fp = &G->fh[ti][0][lane][0];
      const Load e = ffn_load(46 + min(lane, 12 + NT), j, rk);
      uint32_t seen = 0, i = 0, n = 0, win = 1;
      mbar_waitb(BAR(B_RE + 20));
      while (i < 13 + NT) {
        if (__any_sync(~0u, lane - i < win && (seen & e.c0) != e.c0)) {
          const uint2 f = ld_rlx64(fp);
          seen = __ballot_sync(~0u, f.x == par && f.y == par);
          asm volatile("fence.proxy.async.global;" ::: "memory");
        }
        uint32_t m = __ballot_sync(~0u, lane - i < 4u && (seen & e.c0) == e.c0 && mbar_test(sb + e.wait)) >> i;
        win = (m & 1) ? AWIN : 1;
        for (; i < 13 + NT && (m & 1); i++, m >>= 1) {
          if (lane == i) {
            asm volatile("cp.async.bulk.shared::cluster.global.mbarrier::complete_tx::bytes [%0], [%1], 16384, [%2];"
                         ::"r"(sb + e.dst), "l"(&G->h[ti][e.src][0]), "r"(sb + e.full) : "memory");
            TS(3, 48 + i);
          }
          __syncwarp();
        }
        spin_check(n);
      }
    } else {
      const int w = hw - 2;
#pragma unroll 1
      for (int ph = 0; ph < 2; ph++) {
        const uint2* fl = &G->half[2 * ti + w].fo[32 * ph + lane];
        const uint4* src = &G->half[2 * ti + w].o[8 * ph][0];
        const uint32_t fb = BAR((ph ? B_X1F : B_OF) + 4 * w), d1 = sb + 6 * SLOT + w * 24576, d2 = sb + (9 + 2 * w) * SLOT;
        uint32_t n = 0;
        mbar_waitb(BAR(ph ? B_OF + 4 * w + 3 : B_QDONE));
        while (!__all_sync(~0u, (ld_rlx32(fl) & 1) == par)) spin_check(n);
        if (lane == 0) TS(2 + w, 8 + 4 * ph);
        if (AGD) delay(AGD);
#pragma unroll
        for (int p = 1; p < 8; p++) bulk_ld(p < 4 ? d1 + (p - 1) * 8192 : d2 + (p - 4) * 8192, src + (p - (j >= p)) * 512, 8192, fb + 8 * (p / 2));
        if (lane == 0 && (ph || !w)) mbar_arrive_n(BAR(ph ? B_ISS + w : B_ISS + 2), 8);
        if (lane == 0) TS(2 + w, 9 + 4 * ph);
      }
      if (b == 0 && ht == 64) st_rlx32(G->epoch, par);
#pragma unroll 1
      for (int p = 0; p < 4; p++) {
        mbar_waitb(BAR(B_HS + 4 * w + p));
        bulk_st(&G->h[ti][8 * p][(2 * j + w) * (p < 3 ? 512 : 256)], sb + (9 + 2 * w) * SLOT + p * 8192, p < 3 ? 8192 : 4096);
        asm volatile("cp.async.bulk.commit_group;" ::: "memory");
        asm volatile("cp.async.bulk.wait_group 0;" ::: "memory");
        __syncwarp();
        if (lane == 0) {
          if (p >= 2) mbar_arrive_n(BAR(B_HST + 2 * w + p - 2), 2);
          st_rel32(&G->fh[ti][j][p][w], par);
          TS(2 + w, 16 + p);
        }
        __syncwarp();
        if (p == 0) {
#pragma unroll 4
          for (int i = 0; i < 16; i++) G->half[2 * ti + w].y[j ^ 4][i * 32 + lane] = make_uint4(par ^ 1, 0, 0, 0);
        }
      }
      mbar_waitb(BAR(B_DONE));
    }
  } else {
    const int ww = warp & 3, g = lane >> 2, t = lane & 3, tw = tid & 127;
    TSC(22);
    const bool lead = tw == 0;
    uint32_t epoch;
    if (!wg) {
      uint4 wm[4];
      const __nv_bfloat16* wmp = wmod + (size_t)(kq * 128 + ww * 32 + g) * 3072 + cg * 32 + t * 8;
#pragma unroll
      for (int i = 0; i < 4; i++) wm[i] = ldg_nc(wmp + i * 8 * 3072);
      bar_arrive(11, G1 ? 288 : 160);
      asm volatile("barrier.cluster.arrive.relaxed.aligned;" ::: "memory");
      bar_sync(1, 256);
      uint32_t sc[4];
#pragma unroll
      for (int i = 0; i < 4; i++) sc[i] = lds32(sb + OFF_SC + (ww * 32 + i * 8) * 2 + t * 4);
      epoch = lds32(sb + OFF_SC + 256);
      if (epoch != 77) TSC(23);
      float a[4][4];
#pragma unroll
      for (int e = 0; e < 4; e++) {
        a[e][0] = a[e][1] = a[e][2] = a[e][3] = 0.f;
#pragma unroll
        for (int i = 0; i < 4; i += 2) {
          const uint32_t u0 = e == 0 ? wm[i].x : e == 1 ? wm[i].y : e == 2 ? wm[i].z : wm[i].w;
          const uint32_t u1 = e == 0 ? wm[i + 1].x : e == 1 ? wm[i + 1].y : e == 2 ? wm[i + 1].z : wm[i + 1].w;
          hmma(a[e], sc[i], sc[i], sc[i + 1], sc[i + 1], movtrans(u0), movtrans(u1));
        }
      }
      TSC(24);
      if (g < 2) sts128(sb + OFF_RED + ww * 128 + t * 32 + g * 16, __float_as_uint(g ? a[2][0] : a[0][0]), __float_as_uint(g ? a[2][1] : a[0][1]),
                        __float_as_uint(g ? a[3][0] : a[1][0]), __float_as_uint(g ? a[3][1] : a[1][1]));
      bar_arrive(3, 160);
    } else {
      epoch = ld_rlx32(G->epoch);
      const float c = bflo(ldg16(cvec + kq * 128 + tw));
      uint32_t ph[4];
#pragma unroll
      for (int h = 0; h < 4; h++) ph[h] = ldg32(wphi + j * 1024 + h * 256 + 2 * tw);
      if (G1) bar_arrive(11, 288);
      asm volatile("barrier.cluster.arrive.relaxed.aligned;" ::: "memory");
      asm volatile("st.shared.u16 [%0], %1;" ::"r"(sb + OFF_SC + tw * 2), "h"((uint16_t)pack2(c * rcp(1.f + ex2(-1.4426950408889634f * c)), 0.f)) : "memory");
      if (lead) sts32(sb + OFF_SC + 256, epoch);
      bar_arrive(1, 256);
      float* mp = &G->mod[kq][cg * 32 + lane];
      if (ww == 0) st_rlx32(mp, epoch & 1);
      const uint32_t ad = sb + OFF_PHIB + (tw >> 6) * 1024 + (tw & 7) * 128 + ((tw >> 3) & 7) * 16;
#pragma unroll
      for (int h = 0; h < 4; h++) sts128(ad + h * 2048, h == 0 ? ph[0] : 0, h == 1 ? ph[1] : 0, h == 2 ? ph[2] ^ 0x80008000u : 0, h == 3 ? ph[3] ^ 0x80008000u : 0);
      if (ww == 0) {
        bar_sync(3, 160);
        const uint32_t ra = sb + OFF_RED + lane * 4;
        st_rlx32(mp, tagf((U_(lds32(ra)) + U_(lds32(ra + 128))) + (U_(lds32(ra + 256)) + U_(lds32(ra + 384))), ~epoch));
      }
      TSC(0);
    }
    asm volatile("setmaxnreg.inc.sync.aligned.u32 224;");
    const uint32_t par = launch_parity(epoch);
    if (wg) bar_sync(6, 256);
    asm volatile("barrier.cluster.wait.aligned;" ::: "memory");
    uint32_t af[32][4];
    {
      const uint32_t mo = mat_off(ww, lane);
      float sq[6][4];
#pragma unroll
      for (int i = 0; i < 6; i++) sq[i][0] = sq[i][1] = sq[i][2] = sq[i][3] = 0.f;
#pragma unroll
      for (int c = 0; c < 5; c++) {
        if (c < 4) {
          mbar_wait(BAR(B_XF + c) + 32 * wg);
          TSC(40 + c);
          const uint32_t xa = sb + (wg ? x_slot(4 + c) : x_slot(c)) * SLOT;
#pragma unroll
          for (int k = 0; k < 8; k++) ldsm4(af[8 * c + k], xa + (k >> 2) * 8192 + (mo ^ ((k & 3) << 5)));
        }
        if (c == W1AT && !wg) bar_arrive(6, 256);
        if (c) {
#pragma unroll
          for (int kk = 0; kk < 8; kk++) {
            const int k = 8 * c - 8 + kk;
            hmma8(sq[0], af[k][0], af[k][1], af[k][0]);
            hmma8(sq[1], af[k][0], af[k][1], af[k][1]);
            hmma8(sq[2], af[k][2], af[k][3], af[k][2]);
            hmma8(sq[3], af[k][2], af[k][3], af[k][3]);
            hmma(sq[4 + (k & 1)], af[k][0], af[k][1], af[k][2], af[k][3], 0x3f803f80u, 0x3f803f80u);
          }
        }
      }
      fence_async_smem();
      __syncwarp();
      if (lane == 0) {
        mbar_arrive(BAR(B_XE));
        mbar_arrive_pair(BAR(B_XE2), rd);
      }
      TSC(1);
      uint32_t ls[4];
#pragma unroll
      for (int r = 0; r < 2; r++) {
        const float s2 = __shfl_sync(~0u, (g & 1) ? sq[r][2 * r + 1] + sq[2 + r][2 * r + 1] : sq[r][2 * r] + sq[2 + r][2 * r], 4 * g + (g >> 1));
        const float s1 = (sq[4][2 * r] + sq[5][2 * r]) * (1.f / 512);
        const float rs = rsqrtf(fmaxf(s2 * (1.f / 512) - s1 * s1, 0.f) + 1e-5f);
        ls[2 * r] = pack2(rs, rs);
        ls[2 * r + 1] = pack2(-s1 * bflo(ls[2 * r]), -s1 * bflo(ls[2 * r]));
      }
#pragma unroll
      for (int k = 0; k < 32; k++) ln_rows(af[k], ls);
      TSC(27);
      if (wg) bar_sync(10, 256);
      else mbar_wait(BAR(B_MOD1));
      TSC(25);
      const uint32_t ta = sb + OFF_TAB1 + (lane_id() & 3) * 16;
#pragma unroll
      for (int k = 0; k < 32; k++) {
        uint32_t tb[4];
        lds128(tb, ta + k * 64);
        ln_cols(af[k], tb);
        if (k == W1LN && !wg) bar_arrive(10, 256);
        if (k == TW && wg) bar_arrive(7, 256);
      }
      TSC(2);
    }
    {
      float acc[32];
      if (wg) bar_sync(4, 256);
      else if (TW >= 0) bar_sync(7, 256);
      else mbar_wait(BAR(B_XE));
      mbar_wait(BAR(B_WF));
      TSC(28);
      TSG(0);
      pass64<0>(acc, af, sb);
      if (!wg && !PHIK) bar_arrive(4, 256);
#pragma unroll 1
      for (int it = 0; it < 2; it++) {
        wg_wait<0>();
        pin(acc);
        if (lead) mbar_arrive(BAR(B_KDONE + it));
        TSC(3 + 4 * it);
        feature_map(acc, sb, sb + (9 + 2 * wg) * SLOT + ww * 2048, wg, it);
        TSC(4 + 4 * it);
        if (it) break;
        {
          mbar_wait(BAR(B_WF + 2));
          pass64<4>(acc, af, sb);
          mbar_wait(BAR(B_KDONE));
          wg_wait<0>();
          pin(acc);
          TSC(5);
          const uint32_t lane = lane_id(), t = lane & 3;
          const uint32_t va = sb + (lane >> 4) * 2048 + warp * 256 + (lane & 15) * 16;
#pragma unroll
          for (int n = 0; n < 4; n++)
            stsm4(va + (2 * n + (n >= 2)) * 2048, pack2(acc[8 * n], acc[8 * n + 1]), pack2(acc[8 * n + 2], acc[8 * n + 3]),
                  pack2(acc[8 * n + 4], acc[8 * n + 5]), pack2(acc[8 * n + 6], acc[8 * n + 7]));
          if (lane < 16) sts128(va + 4 * 2048, 0x3f803f80u, 0x3f803f80u, 0x3f803f80u, 0x3f803f80u);
          fence_async_smem();
          if (!wg) {
            mbar_wait(BAR(B_ZERO));
            mbar_wait(BAR(B_WF + 3));
          }
          bar_sync(5, 256);
          float kv[20], kw[20];
          wg_fence();
#pragma unroll
          for (int k = 0; k < 4; k++) {
            mma_ss_n40t(kv, mkdesc(sb, 9 * SLOT + k * 2048, 64, 1024, 1, wg * 512), mkdesc(sb, k * 256, 128, 2048, 0, wg * 512), k > 0);
            if (KV2) mma_ss_n40t(kw, mkdesc(sb, 11 * SLOT + k * 2048, 64, 1024, 1, wg * 512), mkdesc(sb, 1024 + k * 256, 128, 2048, 0, wg * 512), k > 0);
            else mma_ss_n40t(kv, mkdesc(sb, 11 * SLOT + k * 2048, 64, 1024, 1, wg * 512), mkdesc(sb, 1024 + k * 256, 128, 2048, 0, wg * 512), 1);
          }
          wg_commit();
          float4* dst = &G->kv[j][warp * 32 + lane];
          wg_wait<0>();
          pin(kv);
          if (KV2) {
            pin(kw);
#pragma unroll
            for (int i = 0; i < 20; i++) kv[i] += kw[i];
          }
          const float z = wg ? (t & 1 ? kv[2] : kv[0]) : (t & 1 ? kv[18] : kv[16]);
#pragma unroll
          for (int i = 0; i < 12; i++) kv[i] = (ww & 2) ? kv[i + 8] : kv[i];
#pragma unroll
          for (int i = 0; i < 8; i++) kv[i] = wg ? kv[i + 4] : kv[i];
          kv[8] = z;
#pragma unroll
          for (int i = 0; i < 3; i++)
            asm volatile("red.relaxed.gpu.global.add.v4.f32 [%0], {%1, %2, %3, %4};" ::"l"(dst + i * 256), "f"(kv[3 * i]), "f"(kv[3 * i + 1]),
                         "f"(kv[3 * i + 2]), "f"(1.f) : "memory");
          if (lead) {
            if (wg) sts32(sb + OFF_RED, clock32());
            mbar_arrive(BAR(B_KVP));
          }
          TSC(6);
          if (wg) bar_sync(4, 256);
          pass64<8>(acc, af, sb);
          mbar_wait(BAR(B_KVP));
        }
      }
      if (NB & 1) __syncwarp();
      else wg_bar(wg);
    }
    Half* const H = &G->half[2 * ti + wg];
    const uint32_t jw = j * 512 + ww * 128;
    mbar_wait(BAR(B_KVB));
    if (HOLD >= 0 && HOLD < 10 && wg) mbar_wait(BAR(HOLD == 4 ? B_ISS + 2 : B_OF + HOLD));
    TSC(9);
    {
      if (EO == 4 || (EO == 6 && wg)) { if (lane == 0) st_rlx32(&H->fo[jw >> 7], par); }
      float nm[4][12];
      wg_fence();
#pragma unroll
      for (int hk = 0; hk < 8; hk++) {
        const int h = NUMO ? hk & 3 : hk >> 1, k = NUMO ? hk >> 2 : hk & 1;
          mma_ss_n24(nm[h], mkdesc(sb, 9 * SLOT + (h >> 1) * 8192 + (h & 1) * 64 + k * 32, 16, 1024, 1, wg * 2048),
                     mkdesc(sb, h * 1536 + k * 768, 384, 128, 0), k > 0);
      }
      wg_commit();
      if (EO == 3 || (EO == 5 && wg)) { if (lane == 0) st_rlx32(&H->fo[jw >> 7], par); }
      if (QH == 6 && !wg) bar_arrive(4, 256);
      uint4* dst = &H->o[0][jw + lane_id()];
      wg_wait<0>();
      if (HOLD >= 10 && wg) mbar_wait(BAR(HOLD == 14 ? B_ISS + 2 : B_OF + HOLD - 10));
      if (EO == 2 || (EO >= 5 && !wg)) { if (lane == 0) st_rlx32(&H->fo[jw >> 7], par); }
#pragma unroll
      for (int h = 0; h < 4; h++) {
        pin(nm[h]);
        const float i0 = rcp(nm[h][8] + 1e-6f), i1 = rcp(nm[h][10] + 1e-6f);
        af[h][0] = tagu(pack2(nm[h][0] * i0, nm[h][1] * i0), par);
        af[h][1] = pack2(nm[h][2] * i1, nm[h][3] * i1);
        af[h][2] = pack2(nm[h][4] * i0, nm[h][5] * i0);
        af[h][3] = pack2(nm[h][6] * i1, nm[h][7] * i1);
        stg128(dst + h * 32, af[h]);
      }
      if (QH == 7 && !wg) bar_arrive(4, 256);
      if (lead) mbar_arrive_pair(BAR(B_NUME), rd);
#pragma unroll
      for (int h = 0; h < 4; h++) af[h][0] &= ~1u;
    }
    TSC(10);
    TSG(2);
    asm volatile("setmaxnreg.inc.sync.aligned.u32 232;");
    const uint32_t fa1 = sb + 6 * SLOT + wg * 24576 + ww * 2048, fa2 = sb + (9 + 2 * wg) * SLOT + ww * 2048;
    uint32_t xlsb;
    {
      const uint32_t lane = lane_id(), g = lane >> 2, t = lane & 3;
      float acc[32];
      uint32_t xq[4][4];
      mbar_wait(BAR(B_XRF));
#pragma unroll
      for (int k = 0; k < 4; k++) ldsm4(xq[k], sb + SLOT + wg * 8192 + (mat_off(ww, lane) ^ (k << 5)));
      if (lane == 0) mbar_arrive_pair(BAR(B_XRE) + ((xq[0][0] | xq[1][0] | xq[2][0] | xq[3][0]) & (j >> 3)), rd);
      mbar_wait(BAR(B_MOD2));
      float2 ga[8];
#pragma unroll
      for (int n = 0; n < 8; n++) ga[n] = lds64f(sb + OFF_GAB + n * 32 + t * 8);
      mbar_wait(BAR(B_WOF));
      wg_fence();
#pragma unroll
      for (int k = 0; k < 4; k++) mma_rs_n64(acc, af[k], mkdesc(sb, 2 * SLOT + k * 2048, 32, 1024, 1), k > 0);
      wg_commit();
      const uint32_t g1 = fa1 + lane * 16, g2 = fa2 + lane * 16;
#define SRC_OFF(p) (((p) - 1 + ((p) - 1 >= j)) * 512 + ww * 128)
      mbar_wait(BAR(B_OF) + 32 * wg);
      TSC(11);
      lds_frags<0, 4, 4>(af, g1);
#pragma unroll
      for (int q = 0; q < 4; q++) {
        if ((CKO & 2) && q) mbar_wait(BAR(B_OF + (q < 3 ? q + 1 : 3)) + 32 * wg);
        if (q) check4(&af[8 * q], &H->o[0][0], SRC_OFF(2 * q), (CKO & 8) ? par | (clock32() << 1) : par);
        check4(&af[8 * q + 4], &H->o[0][0], SRC_OFF(2 * q + 1), par);
        if (q < 3 && (!(CKO & 2) || !q)) mbar_wait(BAR(B_OF + 1 + q) + 32 * wg);
        if (q == 0) lds_frags<0, 8, 8>(af, g1 + 8192);
        if (q == 1) lds_frags<0, 8, 16>(af, g2);
        if (q == 2) lds_frags<0, 8, 24>(af, g2 + 16384);
        wg_fence();
#pragma unroll
        for (int k = 0; k < 8; k++)
          if (q || k >= 4) mma_rs_n64(acc, af[8 * q + k], mkdesc(sb, 2 * SLOT + (8 * q + k) * 2048, 32, 1024, 1), 1);
        wg_commit();
        if (q == 2) {
          wg_wait<1>();
          if (lead) mbar_arrive_pair(BAR(B_WOE), rd);
        }
      }
      if (EX == 3) { if (lane == 0) st_rlx32(&H->fx[jw >> 7], par); }
      wg_wait<0>();
      pin(acc);
      if (EX == 2) { if (lane == 0) st_rlx32(&H->fx[jw >> 7], par); }
      if (lead) mbar_arrive_pair(BAR(B_WOE1), rd);
      TSC(12);
      float s0 = 0.f, s1 = 0.f, q0 = 0.f, q1 = 0.f;
#pragma unroll
      for (int n = 0; n < 8; n++) {
        const uint32_t u = xq[n >> 1][(n & 1) * 2], v = xq[n >> 1][(n & 1) * 2 + 1];
        acc[4 * n] = fmaf(ga[n].x, acc[4 * n], bflo(u));
        acc[4 * n + 1] = fmaf(ga[n].y, acc[4 * n + 1], bfhi(u));
        acc[4 * n + 2] = fmaf(ga[n].x, acc[4 * n + 2], bflo(v));
        acc[4 * n + 3] = fmaf(ga[n].y, acc[4 * n + 3], bfhi(v));
        s0 += acc[4 * n] + acc[4 * n + 1];
        s1 += acc[4 * n + 2] + acc[4 * n + 3];
        q0 = fmaf(acc[4 * n], acc[4 * n], fmaf(acc[4 * n + 1], acc[4 * n + 1], q0));
        q1 = fmaf(acc[4 * n + 2], acc[4 * n + 2], fmaf(acc[4 * n + 3], acc[4 * n + 3], q1));
      }
      s0 = ((t & 1) ? q0 : s0) + __shfl_xor_sync(~0u, (t & 1) ? s0 : q0, 1);
      s1 = ((t & 1) ? q1 : s1) + __shfl_xor_sync(~0u, (t & 1) ? s1 : q1, 1);
      s0 = ((t & 2) ? s1 : s0) + __shfl_xor_sync(~0u, (t & 2) ? s0 : s1, 2);
      if (XH1 >= 0 && wg) mbar_wait(BAR(B_X1F + XH1));
      if (XH0 >= 0 && !wg) mbar_wait(BAR(B_OF + 4 + XH0));
      if (EX == 1) { if (lane == 0) st_rlx32(&H->fx[jw >> 7], par); }
      st_rlx32(&H->st2[0][(jw >> 3) + (t >> 1) * 8 + g].x + (t & 1), tagf(s0, par));
      uint4* dst = &H->x1[0][jw + lane];
      xlsb = 0;
#pragma unroll
      for (int k = 0; k < 4; k++) {
#pragma unroll
        for (int i = 0; i < 4; i++) af[k][i] = pack2(acc[8 * k + 2 * i], acc[8 * k + 2 * i + 1]);
        xlsb |= ((af[k][0] ^ par) & 1) << k;
        af[k][0] = tagu(af[k][0], par);
        stg128(dst + k * 32, af[k]);
        if (EX == -k) { if (lane == 0) st_rlx32(&H->fx[jw >> 7], par); }
      }
      asm volatile("" : "+r"(xlsb));
#pragma unroll
      for (int k = 0; k < 4; k++) af[k][0] &= ~1u;
    }
    TSC(13);
    uint32_t rf = BAR(B_RF);
    {
      uint32_t ls[4];
      const uint32_t lane = lane_id(), ta = sb + OFF_TAB2 + (lane & 3) * 16, g1 = fa1 + lane * 16, g2 = fa2 + lane * 16;
      uint32_t tb[4][4];
#pragma unroll
      for (int k = 0; k < 4; k++) lds128(tb[k], ta + j * 256 + k * 64);
      {
        const uint32_t g = lane >> 2, t = lane & 3;
        const float2* sp = &H->st2[2 * t][ww * 16 + g];
        uint2 a0, a1, b0, b1;
#define ST_BAD(a0, a1, b0, b1) __any_sync(~0u, px4(a0.y, a1.y, b0.y, b1.y, par, px4(a0.x, a1.x, b0.x, b1.x, par)) & 1)
        if (SD) delay(SD);
        do {
          a0 = ld_rlx64(sp); a1 = ld_rlx64(sp + 64); b0 = ld_rlx64(sp + 8); b1 = ld_rlx64(sp + 72);
        } while (ST_BAD(a0, a1, b0, b1));
        TSC(14);
        float m0 = F_(a0.x) + F_(a1.x), m1 = F_(b0.x) + F_(b1.x), v0 = F_(a0.y) + F_(a1.y), v1 = F_(b0.y) + F_(b1.y);
#pragma unroll
        for (int m = 1; m < 4; m <<= 1) {
          m0 += __shfl_xor_sync(~0u, m0, m); m1 += __shfl_xor_sync(~0u, m1, m);
          v0 += __shfl_xor_sync(~0u, v0, m); v1 += __shfl_xor_sync(~0u, v1, m);
        }
        m0 *= 1.f / 512; m1 *= 1.f / 512;
        v0 = rsqrtf(fmaxf(v0 * (1.f / 512) - m0 * m0, 0.f) + 1e-5f);
        v1 = rsqrtf(fmaxf(v1 * (1.f / 512) - m1 * m1, 0.f) + 1e-5f);
        ls[0] = pack2(v0, v0); ls[1] = pack2(-m0 * bflo(ls[0]), -m0 * bflo(ls[0]));
        ls[2] = pack2(v1, v1); ls[3] = pack2(-m1 * bflo(ls[2]), -m1 * bflo(ls[2]));
      }
      float acc[64];
      {
#pragma unroll
        for (int p = 0; p < 8; p++) {
          if (p == 1 && !P1A) {
            mbar_wait(BAR(B_X1F) + 32 * wg);
            lds_frags<0, 4, 4>(af, g1);
          }
          if (CKO & 1) mbar_wait(BAR(B_RF + p));
          if (p) check4(&af[4 * p], &H->x1[0][0], SRC_OFF(p), (CKO & 4) ? par | (clock32() << 1) : par);
          if (p && p < 4 && lane == 0) mbar_arrive_pair(BAR(B_X1E + (p - 1) / 2) + wg * 8 * ((p + 2) / 2 - (p - 1) / 2), rd);
#pragma unroll
          for (int k = 0; k < 4; k++) {
            ln_rows(af[4 * p + k], ls);
            ln_cols(af[4 * p + k], tb[k]);
          }
          if (!(CKO & 1)) mbar_wait(BAR(B_RF + p));
          TSC(32 + p);
          if ((p & 1) && p < 7) mbar_wait(BAR(B_X1F + (p + 1) / 2) + 32 * wg);
          if (p == 0 && P1A) {
            mbar_wait(BAR(B_X1F) + 32 * wg);
            lds_frags<0, 4, 4>(af, g1);
          }
          if (p == 1) lds_frags<0, 4, 8>(af, g1 + 8192);
          if (p == 2) lds_frags<0, 4, 12>(af, g1 + 16384);
          if (p == 3) lds_frags<0, 4, 16>(af, g2);
          if (p == 4) lds_frags<0, 4, 20>(af, g2 + 8192);
          if (p == 5) lds_frags<0, 4, 24>(af, g2 + 16384);
          if (p == 6) lds_frags<0, 4, 28>(af, g2 + 24576);
          if (p < 7 && TBI == 0) {
#pragma unroll
            for (int k = 0; k < 4; k++) lds128(tb[k], ta + (p + (p >= j)) * 256 + k * 64);
          }
          wg_fence();
#pragma unroll
          for (int k = 0; k < 4; k++) {
            mma_rs_n128(acc, af[4 * p + k], mkdesc(sb, p * SLOT + k * 2048, 8192, 1024, 1), p + k > 0);
            if (p < 7 && TBI == 1 && k == 0) {
#pragma unroll
              for (int i = 0; i < 4; i++) lds128(tb[i], ta + (p + (p >= j)) * 256 + i * 64);
            }
            if (p < 7 && TBI == 2 && k < 2) {
#pragma unroll
              for (int i = 0; i < 2; i++) lds128(tb[2 * k + i], ta + (p + (p >= j)) * 256 + (2 * k + i) * 64);
            }
          }
          wg_commit();
          if (p) {
            wg_wait<1>();
            if (lead) mbar_arrive_pair(BAR(B_RE + p - 1), rd);
          }
        }
      }
      rf += 64;
      glu_epilogue(acc, rf + 8 * (B_RE - B_RF) - 8, rd, lead, sb + (9 + 2 * wg) * SLOT, ww, BAR(B_HS) + 32 * wg);
      TSC(15);
      TSG(4);
#pragma unroll 1
      for (int ps = 1; ps < 3; ps++) {
        const uint32_t sl = ps == 1 ? 0x65432108u : 0x54321087u;
#pragma unroll
        for (int p = 0; p < 8; p++) {
          mbar_wait(rf);
          wg_fence();
#pragma unroll
          for (int k = 0; k < 4; k++) mma_rs_n128(acc, af[4 * p + k], mkdesc(sb, k * 2048, 8192, 1024, 1, ((sl >> (4 * p)) & 15) * 1024), p + k > 0);
          wg_commit();
          if (p) {
            wg_wait<1>();
            if (lead) mbar_arrive_pair(rf + 8 * (B_RE - B_RF) - 8, rd);
          }
          rf += 8;
        }
        glu_epilogue(acc, rf + 8 * (B_RE - B_RF) - 8, rd, lead, sb + (9 + 2 * wg) * SLOT + ps * 8192, ww, BAR(B_HS + ps) + 32 * wg);
        TSC(15 + ps);
      }
    }
    {
      float acc[32];
#pragma unroll
      for (int s = 0; s < 4; s++) {
        mbar_wait(BAR(B_RF + 24 + s));
        wg_fence();
#pragma unroll
        for (int k = 0; k < 8; k++)
          mma_rs_n64(acc, af[8 * s + k], mkdesc(sb, ((24 + s) % 9) * SLOT + (k >> 2) * 8192 + (k & 3) * 1024, 4096, 512, 2), s + k > 0);
        wg_commit();
        if (s) {
          wg_wait<1>();
          if (lead) mbar_arrive_pair(BAR(B_RE + 23 + s), rd);
        } else {
          mbar_wait(BAR(B_HS + 2) + 32 * wg);
        }
      }
      wg_wait<0>();
      pin(acc);
      if (lead) mbar_arrive_pair(BAR(B_RE + 27), rd);
      TSC(18);
      TSG(6);
      const uint32_t lane = lane_id(), ha = sb + (9 + 2 * wg) * SLOT + 3 * 8192 + (ww * 16 + (lane & 15)) * 64;
#pragma unroll
      for (int k = 0; k < 2; k++) {
        uint32_t h[4];
#pragma unroll
        for (int i = 0; i < 4; i++)
          h[i] = pack2(fmaxf(acc[8 * k + 2 * i], 0.f) * acc[16 + 8 * k + 2 * i], fmaxf(acc[8 * k + 2 * i + 1], 0.f) * acc[17 + 8 * k + 2 * i]);
        stsm4(ha + (((2 * k + (lane >> 4)) ^ ((lane >> 1) & 3)) << 4), h[0], h[1], h[2], h[3]);
      }
      fence_async_smem();
      __syncwarp();
      if (lane == 0) mbar_arrive_n(BAR(B_HS + 3) + 32 * wg, 2);
    }
    {
      float acc[64];
      const uint32_t lane = lane_id(), t = lane & 3;
      uint4 x1[4];
      const uint4* xp = &H->x1[0][jw + lane];
#pragma unroll
      for (int k = 0; k < 4; k++) x1[k] = xp[k * 32];
      float2 gb[8];
#pragma unroll
      for (int n = 0; n < 8; n++) gb[n] = lds64f(sb + OFF_GAB + 256 + n * 32 + t * 8);
      int u = 28, up = 28;
#pragma unroll 1
      for (int s = 0; s < S_T; s++) {
        const uint32_t aa = s < 3 ? (9 + 2 * wg) * 1024 + s * 512 : (uint32_t)(((slot_pack(31, 2, 8) << 12) >> (4 * s)) & 15) * 1024 + wg * 512;
        const uint32_t bb = (uint32_t)(((slot_pack(28, 1, 3) | slot_pack(32, 2, 8) << 12) >> (4 * s)) & 15) * 1024;
        if (SK && wg && s == SK) bar_sync(6, 256);
        mbar_wait(BAR(B_RF + u));
        TSC(44 + s);
        wg_fence();
#pragma unroll
        for (int k = 0; k < 4; k++)
          mma_ss_n128(acc, mkdesc(sb, k * 32, 16, 1024, 1, aa), mkdesc(sb, k * 2048, 8192, 1024, 1, bb), s + k > 0);
        wg_commit();
        if (SK && !wg && s == SK + SKD) bar_arrive(6, 256);
        wg_wait<1>();
        if (s == 2 || (R13 && s == 3)) mbar_wait(BAR(B_HST - 2) + 16 * wg + 8 * s);
        if (lead && s && (!R13 || NT == 2 || s < 10)) mbar_arrive_pair(BAR(B_RE + up), rd);
        up = u;
        u += s >= 3 ? 2 : 1;
      }
      uint4* yp = &H->y[0][(jw ^ 2048) + lane];
      float tl[32], xf[32];
      uint32_t r[4][4], r2[4][4];
#pragma unroll
      for (int m = 0; m < 2 * NT + 4; m++) {
        const int u0 = U_T + 3 * (m / 2), ua = m < 2 * NT ? u0 + 2 * (m & 1) : u0 + 1 + (m & 1), ub = m < 2 * NT ? u0 + 1 : u0;
        if (m <= 2 * NT - 2 + YAT) {
          if (!(m & 1)) mbar_wait(BAR(B_RF + ub));
          mbar_wait(BAR(B_RF + ua));
        }
        TSC(54 + m);
        if (m == 2 * NT - 2 + YAT) {
#pragma unroll
          for (int v = ua + 1; v < U_N + 6; v++) mbar_wait(BAR(B_RF + v));
#pragma unroll
          for (int k = 0; k < 4; k++) ld_rlx128(r[k], xp + 4096 + k * 32);
        }
        if (m == 0 || m == SAT + 1) wg_fence();
#pragma unroll
        for (int k = 0; k < 4; k++)
          mma_ss_n64(tl, m < 2 * NT ? mkdesc(sb, slot_of(ua) * SLOT + k * 32, 32, 1024, 1, wg * 512)
                                    : mkdesc(sb, slot_of(ua) * SLOT + (k >> 1) * 8192 + (k & 1) * 32, 16, 512, 2, wg * 256),
                     mkdesc(sb, slot_of(ub) * SLOT + (m & 1) * 8192 + k * 2048, 48, 1024, 1), m + k > 0);
        if (NT == 2 && !R13 && m == 1) {
          wg_commit();
          wg_wait<1>();
          if (lead) mbar_arrive_pair(BAR(B_RE + U_T), rd);
        }
        if (m == SAT) {
          wg_commit();
          wg_wait<1>();
          pin(acc);
          if (NT == 2 && lead) mbar_arrive_pair(BAR(B_RE + U_T - 2), rd);
#pragma unroll
          for (int i = 0; i < 4; i++) {
            uint32_t v[4];
#pragma unroll
            for (int e = 0; e < 4; e++) v[e] = pack2(acc[8 * i + 2 * e], acc[8 * i + 2 * e + 1]);
            v[0] = tagu(v[0], par);
            stg128(yp + i * 32, v);
          }
          TSC(63);
        }
      }
      wg_commit();
#pragma unroll
      for (int k = 0; k < 4; k++) {
        const uint32_t v[4] = {x1[k].x ^ ((xlsb >> k) & 1), x1[k].y, x1[k].z, x1[k].w};
#pragma unroll
        for (int i = 0; i < 4; i++) {
          const float2 gg = gb[2 * k + (i >> 1)];
          xf[8 * k + 2 * i] = fmaf(gg.x, acc[32 + 8 * k + 2 * i], bflo(v[i]));
          xf[8 * k + 2 * i + 1] = fmaf(gg.y, acc[33 + 8 * k + 2 * i], bfhi(v[i]));
        }
      }
      pin(xf);
      check4(r, &H->y[0][0], jw, par);
      TSC(20);
#pragma unroll
      for (int k = 0; k < 4; k++)
#pragma unroll
        for (int i = 0; i < 4; i++) {
          const float2 gg = gb[2 * k + (i >> 1)];
          xf[8 * k + 2 * i] = fmaf(gg.x, bflo(r[k][i]), xf[8 * k + 2 * i]);
          xf[8 * k + 2 * i + 1] = fmaf(gg.y, bfhi(r[k][i]), xf[8 * k + 2 * i + 1]);
        }
      const uint32_t oa = R13 ? sb + slot_of(U_T) * SLOT + wg * 8192 : sb + (10 + 2 * wg) * SLOT;
      wg_wait<0>();
      pin(tl);
      TSC(19);
#pragma unroll
      for (int k = 0; k < 4; k++) {
        uint32_t o[4];
#pragma unroll
        for (int i = 0; i < 4; i++) {
          const float2 gg = gb[2 * k + (i >> 1)];
          o[i] = pack2(fmaf(gg.x, tl[8 * k + 2 * i], xf[8 * k + 2 * i]), fmaf(gg.y, tl[8 * k + 2 * i + 1], xf[8 * k + 2 * i + 1]));
        }
        stsm4(oa + (mat_off(ww, lane) ^ (k << 5)), o[0], o[1], o[2], o[3]);
      }
      fence_async_smem();
      __syncwarp();
      if (elect()) {
        asm volatile("cp.async.bulk.tensor.2d.global.shared::cta.bulk_group [%0, {%2, %3}], [%1];"
                     ::"l"(&P.out), "r"(oa + ww * 2048), "r"(j * 64), "r"(ti * 128 + warp * 16) : "memory");
        asm volatile("cp.async.bulk.commit_group;" ::: "memory");
        if (ww == 0) mbar_arrive(BAR(B_DONE));
        asm volatile("cp.async.bulk.wait_group.read 0;" ::: "memory");
      }
      TSC(21);
    }
  }
}

typedef CUresult (*EncodeFn)(CUtensorMap*, CUtensorMapDataType, cuuint32_t, void*, const cuuint64_t*, const cuuint64_t*, const cuuint32_t*,
                             const cuuint32_t*, CUtensorMapInterleave, CUtensorMapSwizzle, CUtensorMapL2promotion, CUtensorMapFloatOOBfill);

void make_map(EncodeFn enc, CUtensorMap* m, const void* p, int cols, int rows, int bc, int br) {
  cuuint64_t gd[2] = {(cuuint64_t)cols, (cuuint64_t)rows}, gs[1] = {(cuuint64_t)cols * 2};
  cuuint32_t bd[2] = {(cuuint32_t)bc, (cuuint32_t)br}, es[2] = {1, 1};
  enc(m, CU_TENSOR_MAP_DATA_TYPE_BFLOAT16, 2, const_cast<void*>(p), gd, gs, bd, es, CU_TENSOR_MAP_INTERLEAVE_NONE,
      bc == 64 ? CU_TENSOR_MAP_SWIZZLE_128B : CU_TENSOR_MAP_SWIZZLE_64B, CU_TENSOR_MAP_L2_PROMOTION_L2_128B, CU_TENSOR_MAP_FLOAT_OOB_FILL_NONE);
}

}

extern "C" void kernel_launch(void* const* d_in, const int* in_sizes, int n_in, void* d_out, int out_size) {
  (void)in_sizes; (void)n_in; (void)out_size;
  static EncodeFn enc = nullptr;
  if (!enc) {
    void* fn = nullptr;
    cudaDriverEntryPointQueryResult q;
    cudaGetDriverEntryPoint("cuTensorMapEncodeTiled", &fn, cudaEnableDefault, &q);
    enc = (EncodeFn)fn;
    cudaFuncSetAttribute(fused_kernel, cudaFuncAttributeMaxDynamicSharedMemorySize, SMEM_BYTES + SMEM_EXTRA);
  }
  Params P;
  void* gp = nullptr;
  cudaGetSymbolAddress(&gp, g_scratch);
  make_map(enc, &P.x, d_in[0], 512, 2048, 64, 128);
  {
    cuuint64_t gd[3] = {64, 2048, 8}, gs[2] = {1024, 128};
    cuuint32_t bd[3] = {64, 64, 2}, es[3] = {1, 1, 1};
    enc(&P.x3, CU_TENSOR_MAP_DATA_TYPE_BFLOAT16, 3, d_in[0], gd, gs, bd, es, CU_TENSOR_MAP_INTERLEAVE_NONE, CU_TENSOR_MAP_SWIZZLE_128B,
        CU_TENSOR_MAP_L2_PROMOTION_L2_128B, CU_TENSOR_MAP_FLOAT_OOB_FILL_NONE);
  }
  make_map(enc, &P.wqkv, d_in[1], 1536, 512, 64, 128);
  make_map(enc, &P.wo, d_in[3], 512, 512, 64, 64);
  make_map(enc, &P.wg, d_in[5], 1792, 512, 64, 64);
  make_map(enc, &P.wu, d_in[6], 1792, 512, 64, 64);
  make_map(enc, &P.wg32, d_in[5], 1792, 512, 32, 64);
  make_map(enc, &P.wu32, d_in[6], 1792, 512, 32, 64);
  make_map(enc, &P.wd, d_in[7], 512, 1792, 64, 64);
  make_map(enc, &P.out, d_out, 512, 2048, 64, 16);
  P.wop = (const __nv_bfloat16*)d_in[3];
  P.wgp = (const __nv_bfloat16*)d_in[5];
  P.wup = (const __nv_bfloat16*)d_in[6];
  P.wdp = (const __nv_bfloat16*)d_in[7];
  fused_kernel<<<128, 384, SMEM_BYTES + SMEM_EXTRA>>>((Scratch*)gp, (const __nv_bfloat16*)d_in[9], (const __nv_bfloat16*)d_in[8], (const __nv_bfloat16*)d_in[2], P);
}
```
